```python
import torch

def _softmax(x, axis=-1):
    return torch.softmax(x, dim=axis)
def _gelu(x):
    return torch.nn.functional.gelu(x, approximate="tanh")
def _silu(x):
    return torch.nn.functional.silu(x)
def _sigmoid(x):
    return torch.sigmoid(x)
def _layernorm(x, axis=-1, eps=1e-5):
    m = x.mean(dim=axis, keepdim=True)
    v = x.var(dim=axis, keepdim=True, unbiased=False)
    return (x - m) / torch.sqrt(v + eps)
def _scatter_add(tgt, idx, src, axis=0):
    return tgt.clone().index_add_(axis, idx, src)
def _segment_sum(src, seg, n):
    out = torch.zeros((n,) + src.shape[1:], dtype=src.dtype)
    return out.index_add_(0, seg, src)
def _pad(x, pw):
    flat = tuple(v for pair in reversed(pw) for v in pair)
    return torch.nn.functional.pad(x, flat)

kernel_name = 'gated_mix__linear_attn_block__mha_block__prompt'

def setup_inputs():

    _w = (lambda a: (lambda t: t.to(torch.bfloat16) if t.is_floating_point() else t)(torch.as_tensor(a)))
    def _A_setup():
        B, S, D = 1, 2048, 576
        return {
            "x": _w((lambda *s: torch.randn(*s, dtype=torch.bfloat16) * 0.05)(B, S, D)),
            "wqkv": _w((lambda *s: torch.randn(*s, dtype=torch.bfloat16) * 0.8)(D, 3 * D)),
            "wo": _w((lambda *s: torch.randn(*s, dtype=torch.bfloat16) * 0.2)(D, D)),
        }
    _A_in = _A_setup()

    def _B_setup():
        B, S, D, H = 1, 2048, 576, 32
        return {
            "x": _w((lambda *s: torch.randn(*s, dtype=torch.bfloat16) * 0.05)(B, S, D)),
            "wqkv": _w((lambda *s: torch.randn(*s, dtype=torch.bfloat16) * 0.8)(D, 3 * D)),
            "wo": _w((lambda *s: torch.randn(*s, dtype=torch.bfloat16) * 0.05)(D, D)),
        }
    _B_in = _B_setup()

    return {
        "A_x": _A_in["x"],
        "A_wqkv": _A_in["wqkv"],
        "A_wo": _A_in["wo"],
        "B_x": _B_in["x"],
        "B_wqkv": _B_in["wqkv"],
        "B_wo": _B_in["wo"],
        "gate_w": _w((lambda *s: torch.randn(*s, dtype=torch.bfloat16) * 0.05)(576) * 16.0),
    }

def reference(A_x, A_wqkv, A_wo, B_x, B_wqkv, B_wo, gate_w):
    def _A_ref(x, wqkv, wo):
        B, S, D = x.shape
        H = 32; Dh = D // H
        qkv = (lambda x, *d: x.permute(*d))((x @ wqkv).reshape(B, S, 3, H, Dh), 2, 0, 3, 1, 4)
        q, k, v = qkv[0], qkv[1], qkv[2]
        phi = lambda t: torch.where(t > 0, t + 1, torch.exp(t)) + 1e-6
        pq, pk = phi(q), phi(k)
        kv = torch.einsum("bhsd,bhse->bhde", pk, v)
        z = torch.einsum("bhsd->bhd", pk)
        num = torch.einsum("bhqd,bhde->bhqe", pq, kv)
        den = torch.einsum("bhqd,bhd->bhq", pq, z)[..., None] + 1e-6
        o = num / den
        return (lambda x, *d: x.permute(*d))(o, 0, 2, 1, 3).reshape(B, S, D) @ wo

    def _B_ref(x, wqkv, wo):
        B, S, D = x.shape
        H = 32
        Dh = D // H
        qkv = (lambda x, *d: x.permute(*d))((x @ wqkv).reshape(B, S, 3, H, Dh), 2, 0, 3, 1, 4)
        q, k, v = qkv[0], qkv[1], qkv[2]
        scores = torch.einsum("bhqd,bhkd->bhqk", q, k) * (Dh ** -0.5)
        p = _softmax(scores, axis=-1)
        o = torch.einsum("bhqk,bhkd->bhqd", p, v)
        return (lambda x, *d: x.permute(*d))(o, 0, 2, 1, 3).reshape(B, S, D) @ wo

    x = A_x
    g = _sigmoid((x * gate_w).sum(-1, keepdims=True))
    a = _A_ref(x, A_wqkv, A_wo)
    b = _B_ref(x, B_wqkv, B_wo)
    return g * a + (1 - g) * b
```

```cpp
#include <cuda_runtime.h>
#include <cuda_bf16.h>
#include <cuda.h>
#include <stdint.h>

#define S_LEN 2048
#define DM 576
#define NH 32
#define DH 18
#define HEAD_ELEMS 49152
#define HEAD_BYTES 98304

#define POLY_MASK 0x2A2A
#define EXP_MAGIC 360.0f

__device__ __align__(1024) __nv_bfloat16 g_T[6 * NH * HEAD_ELEMS];
__device__ float g_nmax[2][8][NH];
__device__ __align__(1024) __nv_bfloat16 g_OA[S_LEN * DM];
__device__ __align__(1024) __nv_bfloat16 g_OB[S_LEN * DM];
__device__ float g_gate[S_LEN];

#define WG_FENCE() asm volatile("wgmma.fence.sync.aligned;\n" ::: "memory")
#define WG_COMMIT() asm volatile("wgmma.commit_group.sync.aligned;\n" ::: "memory")
#define WG_WAIT(n) asm volatile("wgmma.wait_group.sync.aligned %0;\n" :: "n"(n) : "memory")

__device__ __forceinline__ uint64_t mkdesc(uint32_t lo, uint32_t hi) {
    uint64_t d; asm("mov.b64 %0, {%1, %2};" : "=l"(d) : "r"(lo), "r"(hi)); return d;
}
__device__ __forceinline__ uint32_t smem_u32(const void* p) { return (uint32_t)__cvta_generic_to_shared(p); }
__device__ __forceinline__ void mbar_init(uint32_t bar, uint32_t cnt) { asm volatile("mbarrier.init.shared::cta.b64 [%0], %1;" :: "r"(bar), "r"(cnt)); }
__device__ __forceinline__ void mbar_expect_tx(uint32_t bar, uint32_t bytes) { asm volatile("mbarrier.arrive.expect_tx.shared::cta.b64 _, [%0], %1;" :: "r"(bar), "r"(bytes) : "memory"); }
__device__ __forceinline__ void mbar_arrive(uint32_t bar) { asm volatile("mbarrier.arrive.shared::cta.b64 _, [%0];" :: "r"(bar) : "memory"); }
__device__ __forceinline__ void mbar_wait(uint32_t bar, uint32_t parity) {
    asm volatile("{\n.reg .pred p;\nWAIT_%=:\nmbarrier.try_wait.parity.shared::cta.b64 p, [%0], %1;\n@p bra DONE_%=;\nbra WAIT_%=;\nDONE_%=:\n}\n" :: "r"(bar), "r"(parity) : "memory");
}
__device__ __forceinline__ void bulk_g2s(uint32_t dst, const void* src, uint32_t bytes, uint32_t bar) {
    asm volatile("cp.async.bulk.shared::cluster.global.mbarrier::complete_tx::bytes [%0], [%1], %2, [%3];" :: "r"(dst), "l"(src), "r"(bytes), "r"(bar) : "memory");
}
__device__ __forceinline__ void tma_2d(uint32_t dst, const CUtensorMap* map, int c0, int c1, uint32_t bar) {
    asm volatile("cp.async.bulk.tensor.2d.shared::cluster.global.mbarrier::complete_tx::bytes [%0], [%1, {%3, %4}], [%2];"
                 :: "r"(dst), "l"((uint64_t)map), "r"(bar), "r"(c0), "r"(c1) : "memory");
}
__device__ __forceinline__ void named_bar(int id, int n) { asm volatile("bar.sync %0, %1;" :: "r"(id), "r"(n) : "memory"); }
__device__ __forceinline__ void fence_async() { asm volatile("fence.proxy.async.shared::cta;" ::: "memory"); }
__device__ __forceinline__ void pdl_wait() { asm volatile("griddepcontrol.wait;" ::: "memory"); }
__device__ __forceinline__ void pdl_launch() { asm volatile("griddepcontrol.launch_dependents;" ::: "memory"); }

__device__ __forceinline__ float ex2f(float x) { float y; asm("ex2.approx.ftz.f32 %0, %1;" : "=f"(y) : "f"(x)); return y; }
__device__ __forceinline__ uint32_t pack_bf16(float lo, float hi) { uint32_t r; asm("cvt.rn.bf16x2.f32 %0, %1, %2;" : "=r"(r) : "f"(hi), "f"(lo)); return r; }
__device__ __forceinline__ float bf_lo(uint32_t v) { return __uint_as_float(v << 16); }
__device__ __forceinline__ float bf_hi(uint32_t v) { return __uint_as_float(v & 0xFFFF0000u); }
__device__ __forceinline__ float bfr(float x) { return __bfloat162float(__float2bfloat16_rn(x)); }

#define ACC4(a, o) "+f"(a[o]), "+f"(a[o + 1]), "+f"(a[o + 2]), "+f"(a[o + 3])
#define ACC12(a, o) ACC4(a, o), ACC4(a, o + 4), ACC4(a, o + 8)
#define ACC16(a, o) ACC4(a, o), ACC4(a, o + 4), ACC4(a, o + 8), ACC4(a, o + 12)
#define ACC32(a, o) ACC16(a, o), ACC16(a, o + 16)

__device__ __forceinline__ void wgmma_n24_rs(float (&d)[12], uint32_t a0, uint32_t a1, uint32_t a2, uint32_t a3, uint64_t bdesc) {
    asm volatile("{\n.reg .pred p;\nsetp.ne.b32 p, 1, 0;\n"
        "wgmma.mma_async.sync.aligned.m64n24k16.f32.bf16.bf16 "
        "{%0,%1,%2,%3,%4,%5,%6,%7,%8,%9,%10,%11}, {%12,%13,%14,%15}, %16, p, 1, 1, 1;\n}\n"
        : ACC12(d, 0) : "r"(a0), "r"(a1), "r"(a2), "r"(a3), "l"(bdesc));
}
template<int TA, int TB>
__device__ __forceinline__ void wgmma_n24_ss(float (&d)[12], uint64_t adesc, uint64_t bdesc, int acc) {
    asm volatile("{\n.reg .pred p;\nsetp.ne.b32 p, %14, 0;\n"
        "wgmma.mma_async.sync.aligned.m64n24k16.f32.bf16.bf16 "
        "{%0,%1,%2,%3,%4,%5,%6,%7,%8,%9,%10,%11}, %12, %13, p, 1, 1, %15, %16;\n}\n"
        : ACC12(d, 0) : "l"(adesc), "l"(bdesc), "r"(acc), "n"(TA), "n"(TB));
}
template<int ACC>
__device__ __forceinline__ void wgmma_n128_rs(float (&d)[64], uint32_t a0, uint32_t a1, uint32_t a2, uint32_t a3, uint64_t bdesc) {
    asm volatile("{\n.reg .pred p;\nsetp.ne.b32 p, %69, 0;\n"
        "wgmma.mma_async.sync.aligned.m64n128k16.f32.bf16.bf16 "
        "{%0,%1,%2,%3,%4,%5,%6,%7,%8,%9,%10,%11,%12,%13,%14,%15,%16,%17,%18,%19,%20,%21,%22,%23,%24,%25,%26,%27,%28,%29,%30,%31,"
        "%32,%33,%34,%35,%36,%37,%38,%39,%40,%41,%42,%43,%44,%45,%46,%47,%48,%49,%50,%51,%52,%53,%54,%55,%56,%57,%58,%59,%60,%61,%62,%63}, {%64,%65,%66,%67}, %68, p, 1, 1, 0;\n}\n"
        : ACC32(d, 0), ACC32(d, 32) : "r"(a0), "r"(a1), "r"(a2), "r"(a3), "l"(bdesc), "n"(ACC));
}
__device__ __forceinline__ void wgmma_n192_ss(float (&d)[96], uint64_t adesc, uint64_t bdesc, int acc) {
    asm volatile("{\n.reg .pred p;\nsetp.ne.b32 p, %98, 0;\n"
        "wgmma.mma_async.sync.aligned.m64n192k16.f32.bf16.bf16 "
        "{%0,%1,%2,%3,%4,%5,%6,%7,%8,%9,%10,%11,%12,%13,%14,%15,%16,%17,%18,%19,%20,%21,%22,%23,%24,%25,%26,%27,%28,%29,%30,%31,"
        "%32,%33,%34,%35,%36,%37,%38,%39,%40,%41,%42,%43,%44,%45,%46,%47,%48,%49,%50,%51,%52,%53,%54,%55,%56,%57,%58,%59,%60,%61,%62,%63,"
        "%64,%65,%66,%67,%68,%69,%70,%71,%72,%73,%74,%75,%76,%77,%78,%79,%80,%81,%82,%83,%84,%85,%86,%87,%88,%89,%90,%91,%92,%93,%94,%95}, %96, %97, p, 1, 1, 0, 1;\n}\n"
        : ACC32(d, 0), ACC32(d, 32), ACC32(d, 64) : "l"(adesc), "l"(bdesc), "r"(acc));
}
__device__ __forceinline__ void wgmma_n216_ss(float (&d)[108], uint64_t adesc, uint64_t bdesc) {
    asm volatile("{\n.reg .pred p;\nsetp.ne.b32 p, 1, 0;\n"
        "wgmma.mma_async.sync.aligned.m64n216k16.f32.bf16.bf16 "
        "{%0,%1,%2,%3,%4,%5,%6,%7,%8,%9,%10,%11,%12,%13,%14,%15,%16,%17,%18,%19,%20,%21,%22,%23,%24,%25,%26,%27,%28,%29,%30,%31,%32,%33,%34,%35,%36,%37,%38,%39,%40,%41,%42,%43,%44,%45,%46,%47,%48,%49,%50,%51,%52,%53,%54,%55,%56,%57,%58,%59,%60,%61,%62,%63,%64,%65,%66,%67,%68,%69,%70,%71,%72,%73,%74,%75,%76,%77,%78,%79,%80,%81,%82,%83,%84,%85,%86,%87,%88,%89,%90,%91,%92,%93,%94,%95,%96,%97,%98,%99,%100,%101,%102,%103,%104,%105,%106,%107}, %108, %109, p, 1, 1, 0, 1;\n}\n"
        : ACC32(d, 0), ACC32(d, 32), ACC32(d, 64), ACC12(d, 96) : "l"(adesc), "l"(bdesc));
}
__device__ __forceinline__ void wgmma_n72_ss(float (&d)[36], uint64_t adesc, uint64_t bdesc, int acc) {
    asm volatile("{\n.reg .pred p;\nsetp.ne.b32 p, %38, 0;\n"
        "wgmma.mma_async.sync.aligned.m64n72k16.f32.bf16.bf16 "
        "{%0,%1,%2,%3,%4,%5,%6,%7,%8,%9,%10,%11,%12,%13,%14,%15,%16,%17,%18,%19,%20,%21,%22,%23,%24,%25,%26,%27,%28,%29,%30,%31,"
        "%32,%33,%34,%35}, %36, %37, p, 1, 1, 0, 1;\n}\n"
        : ACC32(d, 0), ACC4(d, 32) : "l"(adesc), "l"(bdesc), "r"(acc));
}
template<int N> __device__ __forceinline__ void fence_regs(float (&d)[N]) {
    #pragma unroll
    for (int i = 0; i < N; i++) asm volatile("" : "+f"(d[i]) :: "memory");
}

#define K1_STAGES 3
#define K1_STAGE_BYTES 61440
#define K1_SMEM (K1_STAGES * K1_STAGE_BYTES + 1024)
#define STG_PITCH 436

__device__ __forceinline__ float phi_ref(float t) {
    float r = t > 0.f ? bfr(t + 1.0f) : bfr(ex2f(t * 1.4426950408889634f));
    return bfr(r + 1e-6f);
}

__device__ __forceinline__ void qkv_epilogue(const unsigned char* stg, uint32_t* s_nmax, int m0, int n0, int mt, int branch) {
    const int lane = threadIdx.x & 31;
    __syncthreads();
    {
        const float qscale = 0.23570226039551584f * 1.4426950408889634f;
        const int wid = threadIdx.x >> 5;
        #pragma unroll 1
        for (int it = wid; it < 96; it += 8) {
            const int row = (it & 7) * 32 + lane, hh = it >> 3;
            const int srow = m0 + row;
            const int col0 = n0 + hh * 18;
            const int type = col0 / 576, head = (col0 % 576) / 18;
            const int kind = branch * 3 + type;
            uint32_t w[9];
            const uint32_t* src = (const uint32_t*)(stg + row * STG_PITCH + hh * 36);
            #pragma unroll
            for (int i = 0; i < 9; i++) w[i] = src[i];
            uint32_t pad = 0;
            if (kind <= 1) {
                #pragma unroll
                for (int i = 0; i < 9; i++) w[i] = pack_bf16(phi_ref(bf_lo(w[i])), phi_ref(bf_hi(w[i])));
            } else if (kind == 3) {
                #pragma unroll
                for (int i = 0; i < 9; i++) w[i] = pack_bf16(bf_lo(w[i]) * qscale, bf_hi(w[i]) * qscale);
            } else if (kind == 4) {
                pad = ((POLY_MASK >> (2 * ((srow & 63) >> 3) + (srow & 1))) & 1) ? 0x43B43F80u : 0x00003F80u;
            } else {
                pad = 0x00003F80u;
            }
            if (kind == 3 || kind == 4) {
                float n2 = 0.f;
                #pragma unroll
                for (int i = 0; i < 9; i++) { float a = bf_lo(w[i]), b = bf_hi(w[i]); n2 = fmaf(a, a, n2); n2 = fmaf(b, b, n2); }
                uint32_t nb = __float_as_uint(n2);
                if (!(n2 >= 0.f)) nb = 0x7F800000u;
                nb = __reduce_max_sync(0xFFFFFFFFu, nb);
                if (lane == 0) atomicMax(&s_nmax[hh], nb);
            }
            uint4* dst = (uint4*)(g_T + ((size_t)(kind * NH + head)) * HEAD_ELEMS + (srow >> 3) * 192 + (srow & 7) * 8);
            dst[0] = make_uint4(w[0], w[1], w[2], w[3]);
            dst[8] = make_uint4(w[4], w[5], w[6], w[7]);
            dst[16] = make_uint4(w[8], pad, 0u, 0u);
        }
        __syncthreads();
        if (threadIdx.x < 12 && branch == 1) {
            const int col0 = n0 + threadIdx.x * 18;
            const int type = col0 / 576, head = (col0 % 576) / 18;
            if (type < 2) g_nmax[type][mt][head] = __uint_as_float(s_nmax[threadIdx.x]);
        }
    }
}

__global__ void __launch_bounds__(256, 1)
qkv_kernel(const __grid_constant__ CUtensorMap mapX, const __grid_constant__ CUtensorMap mapWA, const __grid_constant__ CUtensorMap mapWA2,
           const __grid_constant__ CUtensorMap mapWB, const __grid_constant__ CUtensorMap mapWB2) {
    extern __shared__ unsigned char smem_raw[];
    __shared__ __align__(8) uint64_t bars[2 * K1_STAGES];
    __shared__ uint32_t s_nmax[12];
    const uint32_t sbase = (smem_u32(smem_raw) + 1023u) & ~1023u;
    unsigned char* stg = smem_raw + (sbase - smem_u32(smem_raw));
    const uint32_t full0 = smem_u32(bars), empty0 = full0 + 8 * K1_STAGES;
    const int mt = blockIdx.x >> 4, nt = blockIdx.x & 15;
    const int branch = nt >> 3, n0 = (nt & 7) * 216, m0 = mt * 256;
    const int wg = threadIdx.x >> 7;
    const int warp = (threadIdx.x >> 5) & 3, lane = threadIdx.x & 31, g = lane >> 2, t = lane & 3;
    const CUtensorMap* w1 = branch ? &mapWB : &mapWA;
    const CUtensorMap* w2 = branch ? &mapWB2 : &mapWA2;
    auto issue = [&](int kt) {
        const int s = kt % K1_STAGES;
        const uint32_t st = sbase + s * K1_STAGE_BYTES, fb = full0 + 8 * s;
        mbar_expect_tx(fb, K1_STAGE_BYTES);
        tma_2d(st, &mapX, kt * 64, m0, fb);
        tma_2d(st + 32768, w1, n0, kt * 64, fb);
        tma_2d(st + 32768 + 8192, w1, n0 + 64, kt * 64, fb);
        tma_2d(st + 32768 + 16384, w1, n0 + 128, kt * 64, fb);
        tma_2d(st + 32768 + 24576, w2, n0 + 192, kt * 64, fb);
    };
    if (threadIdx.x == 0) {
        for (int i = 0; i < K1_STAGES; i++) { mbar_init(full0 + 8 * i, 1); mbar_init(empty0 + 8 * i, 2); }
        asm volatile("fence.mbarrier_init.release.cluster;" ::: "memory");
        issue(0); issue(1); issue(2);
    }
    if (threadIdx.x < 12) s_nmax[threadIdx.x] = 0;
    __syncthreads();
    pdl_launch();
    const uint32_t hiA = 64u | 0x40000000u;
    const uint32_t hiB = 64u | 0x40000000u;
    const uint32_t hiB2 = 32u | 0x80000000u;
    float acc0[96], acc1[96], acd0[12], acd1[12];
    #pragma unroll
    for (int i = 0; i < 96; i++) { acc0[i] = 0.f; acc1[i] = 0.f; }
    #pragma unroll
    for (int i = 0; i < 12; i++) { acd0[i] = 0.f; acd1[i] = 0.f; }
    fence_regs(acc0); fence_regs(acc1); fence_regs(acd0); fence_regs(acd1);
    #pragma unroll 1
    for (int kt = 0; kt < 9; kt++) {
        const int s = kt % K1_STAGES;
        mbar_wait(full0 + 8 * s, (kt / K1_STAGES) & 1);
        const uint32_t st = sbase + s * K1_STAGE_BYTES;
        const uint32_t a_lo = ((st + wg * 16384) >> 4) | (1u << 16);
        const uint32_t b_lo = ((st + 32768) >> 4) | (512u << 16);
        const uint32_t b2_lo = ((st + 32768 + 24576) >> 4) | (1u << 16);
        WG_FENCE();
        #pragma unroll
        for (int kk = 0; kk < 4; kk++) {
            wgmma_n192_ss(acc0, mkdesc(a_lo + kk * 2, hiA), mkdesc(b_lo + kk * 128, hiB), 1);
            wgmma_n24_ss<0, 1>(acd0, mkdesc(a_lo + kk * 2, hiA), mkdesc(b2_lo + kk * 64, hiB2), 1);
            wgmma_n192_ss(acc1, mkdesc(a_lo + 512 + kk * 2, hiA), mkdesc(b_lo + kk * 128, hiB), 1);
            wgmma_n24_ss<0, 1>(acd1, mkdesc(a_lo + 512 + kk * 2, hiA), mkdesc(b2_lo + kk * 64, hiB2), 1);
        }
        WG_COMMIT();
        WG_WAIT(1);
        if (kt > 0) {
            const int sp = (kt - 1) % K1_STAGES;
            if ((threadIdx.x & 127) == 0) mbar_arrive(empty0 + 8 * sp);
            if (threadIdx.x == 0 && kt + 2 < 9) { mbar_wait(empty0 + 8 * sp, ((kt - 1) / K1_STAGES) & 1); issue(kt + 2); }
            __syncwarp();
        }
    }
    WG_WAIT(0);
    fence_regs(acc0); fence_regs(acc1); fence_regs(acd0); fence_regs(acd1);
    __syncthreads();
    {
        unsigned char* r0 = stg + (wg * 128 + warp * 16 + g) * STG_PITCH + t * 4;
        #pragma unroll
        for (int j = 0; j < 24; j++) {
            *(uint32_t*)(r0 + j * 16) = pack_bf16(acc0[4 * j], acc0[4 * j + 1]);
            *(uint32_t*)(r0 + 8 * STG_PITCH + j * 16) = pack_bf16(acc0[4 * j + 2], acc0[4 * j + 3]);
            *(uint32_t*)(r0 + 64 * STG_PITCH + j * 16) = pack_bf16(acc1[4 * j], acc1[4 * j + 1]);
            *(uint32_t*)(r0 + 72 * STG_PITCH + j * 16) = pack_bf16(acc1[4 * j + 2], acc1[4 * j + 3]);
        }
        #pragma unroll
        for (int j = 0; j < 3; j++) {
            *(uint32_t*)(r0 + 384 + j * 16) = pack_bf16(acd0[4 * j], acd0[4 * j + 1]);
            *(uint32_t*)(r0 + 8 * STG_PITCH + 384 + j * 16) = pack_bf16(acd0[4 * j + 2], acd0[4 * j + 3]);
            *(uint32_t*)(r0 + 64 * STG_PITCH + 384 + j * 16) = pack_bf16(acd1[4 * j], acd1[4 * j + 1]);
            *(uint32_t*)(r0 + 72 * STG_PITCH + 384 + j * 16) = pack_bf16(acd1[4 * j + 2], acd1[4 * j + 3]);
        }
    }
    qkv_epilogue(stg, s_nmax, m0, n0, mt, branch);
}

#define PSC 2.465190328815662e-32f
#define PC0 (-1.914111852645874f * PSC)
#define PC1 (0.019580909982323647f * PSC)
#define PC2 (-0.3431040346622467f * PSC)
#define PC3 (-0.07802456617355347f * PSC)
__device__ __forceinline__ float poly_ex2(float t) {
    uint32_t tb = __float_as_uint(t);
    float fc = __uint_as_float(tb & 0xFF807FFFu) - 256.5f;
    float q = fmaf(fc, PC3, PC2);
    q = fmaf(fc, q, PC1);
    q = fmaf(fc, q, PC0);
    return __uint_as_float((tb << 8) + __float_as_uint(q));
}

template<int B0, int NB>
__device__ __forceinline__ void softmax_blocks(float (&s)[64], uint32_t (&p)[32]) {
    #pragma unroll
    for (int i = B0 * 4; i < (B0 + NB) * 4; i++) asm volatile("" : "+f"(s[i]) :: "memory");
    #pragma unroll
    for (int b = B0; b < B0 + NB; b++) {
        float e[4];
        #pragma unroll
        for (int i = 0; i < 4; i++) {
            const bool poly = (POLY_MASK >> (2 * (b & 7) + (i & 1))) & 1;
            e[i] = poly ? poly_ex2(s[4 * b + i]) : ex2f(s[4 * b + i]);
        }
        p[2 * b + 0] = pack_bf16(e[0], e[1]);
        p[2 * b + 1] = pack_bf16(e[2], e[3]);
    }
}

__device__ __forceinline__ void store_o(__nv_bfloat16* O, int row0, int h, int t, const float (&o)[12], float r0, float r1) {
    uint32_t* o0 = (uint32_t*)(O + (size_t)row0 * DM + h * DH);
    uint32_t* o1 = (uint32_t*)(O + (size_t)(row0 + 8) * DM + h * DH);
    o0[t] = pack_bf16(o[0] * r0, o[1] * r0); o1[t] = pack_bf16(o[2] * r1, o[3] * r1);
    o0[t + 4] = pack_bf16(o[4] * r0, o[5] * r0); o1[t + 4] = pack_bf16(o[6] * r1, o[7] * r1);
    if (t == 0) { o0[8] = pack_bf16(o[8] * r0, o[9] * r0); o1[8] = pack_bf16(o[10] * r1, o[11] * r1); }
}

#define K2_SMEM (2 * HEAD_BYTES + 9216 + 1024)

__global__ void __launch_bounds__(512, 1)
attn_kernel(const __nv_bfloat16* __restrict__ x, const __nv_bfloat16* __restrict__ gate_w) {
    extern __shared__ unsigned char smem_raw[];
    __shared__ __align__(8) uint64_t bars[8];
    const uint32_t sK = (smem_u32(smem_raw) + 1023u) & ~1023u;
    const uint32_t sV = sK + HEAD_BYTES;
    unsigned char* sgen = smem_raw + (sK - smem_u32(smem_raw));
    const uint32_t bar0 = smem_u32(bars);
    const int wg = threadIdx.x >> 7, warp = (threadIdx.x >> 5) & 3, lane = threadIdx.x & 31, g = lane >> 2, t = lane & 3;
    if (threadIdx.x == 0) {
        for (int i = 0; i < 8; i++) mbar_init(bar0 + 8 * i, 1);
        asm volatile("fence.mbarrier_init.release.cluster;" ::: "memory");
    }
    __syncthreads();
    pdl_launch();
    const uint32_t kd0 = (sK >> 4) | (8u << 16);
    const uint32_t kd1 = ((sK + 256) >> 4);
    const uint32_t khi = 24;
    const uint32_t vd0 = (sV >> 4) | (24u << 16);
    const uint32_t vhi = 8;

    if (blockIdx.x >= 128) {
        const int a = blockIdx.x - 128;
        {
            const int wid = threadIdx.x >> 5;
            uint32_t gw[9];
            #pragma unroll
            for (int i = 0; i < 9; i++) gw[i] = ((const uint32_t*)gate_w)[lane + 32 * i];
            for (int r = a * 512 + wid; r < a * 512 + 512; r += 16) {
                const uint32_t* xr = (const uint32_t*)(x + (size_t)r * DM);
                float sum = 0.f;
                #pragma unroll
                for (int i = 0; i < 9; i++) {
                    uint32_t xv = xr[lane + 32 * i];
                    sum += bfr(bf_lo(xv) * bf_lo(gw[i])) + bfr(bf_hi(xv) * bf_hi(gw[i]));
                }
                #pragma unroll
                for (int o = 16; o > 0; o >>= 1) sum += __shfl_xor_sync(~0u, sum, o);
                if (lane == 0) {
                    float z = bfr(sum);
                    g_gate[r] = bfr(1.0f / (1.0f + __expf(-z)));
                }
            }
        }
        pdl_wait();
        float* s_part = (float*)(sgen + 2 * HEAD_BYTES);
        __nv_bfloat16* s_kv = (__nv_bfloat16*)(sgen + 2 * HEAD_BYTES + 6912);
        const uint32_t skv = sK + 2 * HEAD_BYTES + 6912;
        uint32_t ph = 0;
        for (int hi = 0; hi < 8; hi++) {
            const int h = a * 8 + hi;
            if (threadIdx.x == 0) {
                mbar_expect_tx(bar0, 2 * HEAD_BYTES);
                for (int i = 0; i < 4; i++) {
                    bulk_g2s(sK + i * 24576, (const char*)(g_T + (size_t)(1 * NH + h) * HEAD_ELEMS) + i * 24576, 24576, bar0);
                    bulk_g2s(sV + i * 24576, (const char*)(g_T + (size_t)(2 * NH + h) * HEAD_ELEMS) + i * 24576, 24576, bar0);
                }
            }
            mbar_wait(bar0, ph);
            float d1[12];
            #pragma unroll
            for (int i = 0; i < 12; i++) d1[i] = 0.f;
            fence_regs(d1);
            WG_FENCE();
            #pragma unroll 4
            for (int ks = 0; ks < 32; ks++) {
                const uint32_t off = (wg * 32 + ks) * 48;
                wgmma_n24_ss<1, 1>(d1, mkdesc(((sK >> 4) | (24u << 16)) + off, 8u), mkdesc(vd0 + off, vhi), 1);
            }
            WG_COMMIT();
            WG_WAIT(0);
            fence_regs(d1);
            if (warp == 0 || (warp == 1 && g < 2)) {
                float* pr = s_part + wg * 432 + (warp * 16 + g) * 24 + 2 * t;
                #pragma unroll
                for (int j = 0; j < 3; j++) { pr[8 * j] = d1[4 * j]; pr[8 * j + 1] = d1[4 * j + 1]; }
                if (warp == 0) {
                    #pragma unroll
                    for (int j = 0; j < 3; j++) { pr[8 * 24 + 8 * j] = d1[4 * j + 2]; pr[8 * 24 + 8 * j + 1] = d1[4 * j + 3]; }
                }
            }
            __syncthreads();
            if (threadIdx.x == 0) {
                mbar_expect_tx(bar0 + 8, HEAD_BYTES);
                for (int i = 0; i < 4; i++)
                    bulk_g2s(sK + i * 24576, (const char*)(g_T + (size_t)(0 * NH + h) * HEAD_ELEMS) + i * 24576, 24576, bar0 + 8);
            }
            for (int i = threadIdx.x; i < 768; i += 512) {
                const int d = i / 24, e = i % 24;
                float v = 0.f;
                if (d < 18) v = s_part[d * 24 + e] + s_part[432 + d * 24 + e] + s_part[864 + d * 24 + e] + s_part[1296 + d * 24 + e];
                s_kv[(d >> 3) * 192 + (e >> 3) * 64 + (d & 7) * 8 + (e & 7)] = __float2bfloat16_rn(v);
            }
            fence_async();
            __syncthreads();
            mbar_wait(bar0 + 8, ph);
            #pragma unroll 1
            for (int mtile = wg; mtile < 32; mtile += 4) {
                float d2[12];
                #pragma unroll
                for (int i = 0; i < 12; i++) d2[i] = 0.f;
                fence_regs(d2);
                WG_FENCE();
                wgmma_n24_ss<0, 1>(d2, mkdesc(kd0 + mtile * 192, khi), mkdesc((skv >> 4) | (24u << 16), vhi), 1);
                wgmma_n24_ss<0, 1>(d2, mkdesc(kd1 + mtile * 192, khi), mkdesc(((skv + 768) >> 4) | (24u << 16), vhi), 1);
                WG_COMMIT();
                WG_WAIT(0);
                fence_regs(d2);
                float l0 = __shfl_sync(~0u, d2[8], (lane & ~3) | 1);
                float l1 = __shfl_sync(~0u, d2[10], (lane & ~3) | 1);
                l0 = bfr(bfr(l0) + 1e-6f); l1 = bfr(bfr(l1) + 1e-6f);
                #pragma unroll
                for (int i = 0; i < 12; i++) d2[i] = __fdividef(bfr(d2[i]), (i & 2) ? l1 : l0);
                store_o(g_OA, mtile * 64 + warp * 16 + g, h, t, d2, 1.0f, 1.0f);
            }
            __syncthreads();
            ph ^= 1;
        }
        return;
    }

    const int h = blockIdx.x >> 2, quarter = blockIdx.x & 3;
    pdl_wait();
    if (threadIdx.x == 0) {
        const char* Kp = (const char*)(g_T + (size_t)(4 * NH + h) * HEAD_ELEMS);
        const char* Vp = (const char*)(g_T + (size_t)(5 * NH + h) * HEAD_ELEMS);
        for (int i = 0; i < 8; i++) {
            mbar_expect_tx(bar0 + 8 * i, 24576);
            bulk_g2s(sK + i * 12288, Kp + i * 12288, 12288, bar0 + 8 * i);
            bulk_g2s(sV + i * 12288, Vp + i * 12288, 12288, bar0 + 8 * i);
        }
    }
    float qm2 = 0.f, km2 = 0.f;
    #pragma unroll
    for (int i = 0; i < 8; i++) { qm2 = fmaxf(qm2, g_nmax[0][i][h]); km2 = fmaxf(km2, g_nmax[1][i][h]); }
    const bool fast = __all_sync(0xFFFFFFFFu, (sqrtf(qm2 * km2) * 1.01f + 0.01f) * 2.0f <= 100.0f);
    uint32_t zr = 0u;
    asm volatile("" : "+r"(zr));
    uint32_t qf[2][6];
    #pragma unroll
    for (int pass = 0; pass < 2; pass++) {
        const int row0 = quarter * 512 + (wg * 2 + pass) * 64 + warp * 16 + g;
        const uint32_t* q0 = (const uint32_t*)(g_T + (size_t)(3 * NH + h) * HEAD_ELEMS + (row0 >> 3) * 192 + (row0 & 7) * 8) + t;
        qf[pass][0] = q0[0]; qf[pass][1] = q0[96]; qf[pass][2] = q0[32]; qf[pass][3] = q0[128];
        qf[pass][4] = q0[64]; qf[pass][5] = q0[160];
    }

    #pragma unroll 1
    for (int pass = 0; pass < 2; pass++) {
        const int row0 = quarter * 512 + (wg * 2 + pass) * 64 + warp * 16 + g;
        uint32_t qa[6];
        #pragma unroll
        for (int i = 0; i < 6; i++) qa[i] = pass ? qf[1][i] : qf[0][i];
        float o[12];
        #pragma unroll
        for (int i = 0; i < 12; i++) o[i] = 0.f;
        fence_regs(o);
        float s[64]; uint32_t p[32];
        #pragma unroll
        for (int i = 0; i < 64; i++) s[i] = 0.f;
        fence_regs(s);
        if (fast) {
            auto sq = [](uint32_t v) { float a = bf_lo(v), b = bf_hi(v); return a * a + b * b; };
            float n0 = sq(qa[0]) + sq(qa[2]) + sq(qa[4]);
            float n1 = sq(qa[1]) + sq(qa[3]) + sq(qa[5]);
            n0 += __shfl_xor_sync(~0u, n0, 1); n0 += __shfl_xor_sync(~0u, n0, 2);
            n1 += __shfl_xor_sync(~0u, n1, 1); n1 += __shfl_xor_sync(~0u, n1, 2);
            const float m0 = sqrtf(n0 * km2) * 1.01f + 0.01f, m1 = sqrtf(n1 * km2) * 1.01f + 0.01f;
            if (t == 1) { qa[4] = pack_bf16(-m0, 1.0f); qa[5] = pack_bf16(-m1, 1.0f); }
            #pragma unroll 1
            for (int j = 0; j < 16; j++) {
                if (pass == 0 && (j & 1) == 0) mbar_wait(bar0 + 8 * (j >> 1), 0);
                const uint32_t ko = j * 384;
                WG_FENCE();
                wgmma_n128_rs<0>(s, qa[0], qa[1], qa[2], qa[3], mkdesc(kd0 + ko, khi));
                wgmma_n128_rs<1>(s, qa[4], qa[5], zr, zr, mkdesc(kd1 + ko, khi));
                WG_COMMIT();
                WG_WAIT(0);
                #pragma unroll
                for (int qd = 0; qd < 4; qd++) {
                    if (qd == 0) softmax_blocks<0, 4>(s, p);
                    if (qd == 1) softmax_blocks<4, 4>(s, p);
                    if (qd == 2) softmax_blocks<8, 4>(s, p);
                    if (qd == 3) softmax_blocks<12, 4>(s, p);
                    WG_FENCE();
                    wgmma_n24_rs(o, p[qd * 8 + 0], p[qd * 8 + 1], p[qd * 8 + 2], p[qd * 8 + 3], mkdesc(vd0 + ko + qd * 96, vhi));
                    wgmma_n24_rs(o, p[qd * 8 + 4], p[qd * 8 + 5], p[qd * 8 + 6], p[qd * 8 + 7], mkdesc(vd0 + ko + qd * 96 + 48, vhi));
                    WG_COMMIT();
                }
                WG_WAIT(0);
            }
        } else {
            float mr0 = -INFINITY, mr1 = -INFINITY;
            #pragma unroll 1
            for (int j = 0; j < 16; j++) {
                if (pass == 0 && (j & 1) == 0) mbar_wait(bar0 + 8 * (j >> 1), 0);
                const uint32_t ko = j * 384;
                WG_FENCE();
                wgmma_n128_rs<0>(s, qa[0], qa[1], qa[2], qa[3], mkdesc(kd0 + ko, khi));
                wgmma_n128_rs<1>(s, qa[4], qa[5], zr, zr, mkdesc(kd1 + ko, khi));
                WG_COMMIT();
                WG_WAIT(0);
                fence_regs(s); fence_regs(o);
                float x0 = mr0, x1 = mr1;
                #pragma unroll
                for (int b = 0; b < 16; b++) {
                    x0 = fmaxf(x0, fmaxf(s[4 * b], s[4 * b + 1]));
                    x1 = fmaxf(x1, fmaxf(s[4 * b + 2], s[4 * b + 3]));
                }
                x0 = fmaxf(x0, __shfl_xor_sync(~0u, x0, 1)); x0 = fmaxf(x0, __shfl_xor_sync(~0u, x0, 2));
                x1 = fmaxf(x1, __shfl_xor_sync(~0u, x1, 1)); x1 = fmaxf(x1, __shfl_xor_sync(~0u, x1, 2));
                const float c0 = exp2f(mr0 - x0), c1 = exp2f(mr1 - x1);
                mr0 = x0; mr1 = x1;
                #pragma unroll
                for (int i = 0; i < 12; i++) o[i] *= (i & 2) ? c1 : c0;
                #pragma unroll
                for (int b = 0; b < 16; b++) {
                    p[2 * b] = pack_bf16(exp2f(s[4 * b] - x0), exp2f(s[4 * b + 1] - x0));
                    p[2 * b + 1] = pack_bf16(exp2f(s[4 * b + 2] - x1), exp2f(s[4 * b + 3] - x1));
                }
                fence_regs(o);
                WG_FENCE();
                #pragma unroll
                for (int kk = 0; kk < 8; kk++)
                    wgmma_n24_rs(o, p[kk * 4 + 0], p[kk * 4 + 1], p[kk * 4 + 2], p[kk * 4 + 3], mkdesc(vd0 + ko + kk * 48, vhi));
                WG_COMMIT();
                WG_WAIT(0);
            }
        }
        fence_regs(o);
        const float l0 = __shfl_sync(~0u, o[8], (lane & ~3) | 1);
        const float l1 = __shfl_sync(~0u, o[10], (lane & ~3) | 1);
        store_o(g_OB, row0, h, t, o, 1.0f / l0, 1.0f / l1);
    }
}

#define K3_WBYTES 82944
#define K3_STAGES 3
#define K3_SMEM (2 * K3_WBYTES + K3_STAGES * 16384 + 1024)

__global__ void __launch_bounds__(288, 1)
out_kernel(const __grid_constant__ CUtensorMap mapOA, const __grid_constant__ CUtensorMap mapOB,
           const __nv_bfloat16* __restrict__ woA, const __nv_bfloat16* __restrict__ woB, __nv_bfloat16* __restrict__ out) {
    extern __shared__ unsigned char smem_raw[];
    __shared__ __align__(8) uint64_t bars[2 * K3_STAGES];
    const uint32_t sA = (smem_u32(smem_raw) + 1023u) & ~1023u;
    const uint32_t sW = sA + K3_STAGES * 16384;
    const uint32_t full0 = smem_u32(bars), empty0 = full0 + 8 * K3_STAGES;
    const int mt = blockIdx.x >> 3, nt = blockIdx.x & 7;
    const int m0 = mt * 128, n0 = nt * 72;
    if (threadIdx.x == 0) {
        for (int i = 0; i < K3_STAGES; i++) { mbar_init(full0 + 8 * i, 1); mbar_init(empty0 + 8 * i, 2); }
        asm volatile("fence.mbarrier_init.release.cluster;" ::: "memory");
    }
    for (int i = threadIdx.x; i < 2 * 5184; i += 288) {
        const int b = i >= 5184, r = b ? i - 5184 : i;
        const int k = r / 9, c = r % 9;
        const __nv_bfloat16* src = (b ? woB : woA) + (size_t)k * DM + n0 + c * 8;
        asm volatile("cp.async.cg.shared.global [%0], [%1], 16;" :: "r"(sW + b * K3_WBYTES + c * 9216 + k * 16), "l"(src) : "memory");
    }
    asm volatile("cp.async.wait_all;" ::: "memory");
    fence_async();
    __syncthreads();
    pdl_wait();
    const int wg = threadIdx.x >> 7;
    if (wg == 2) {
        if (threadIdx.x == 256) {
            for (int c = 0; c < 18; c++) {
                const int s = c % K3_STAGES;
                if (c >= K3_STAGES) mbar_wait(empty0 + 8 * s, ((c / K3_STAGES) - 1) & 1);
                mbar_expect_tx(full0 + 8 * s, 16384);
                tma_2d(sA + s * 16384, c < 9 ? &mapOA : &mapOB, (c % 9) * 64, m0, full0 + 8 * s);
            }
        }
    } else {
        const int warp = (threadIdx.x >> 5) & 3, lane = threadIdx.x & 31, g = lane >> 2, t = lane & 3;
        float aa[36], ab[36];
        #pragma unroll
        for (int i = 0; i < 36; i++) { aa[i] = 0.f; ab[i] = 0.f; }
        fence_regs(aa); fence_regs(ab);
        const uint32_t hiA = 64u | 0x40000000u;
        const uint32_t hiB = 576u;
        #pragma unroll 1
        for (int c = 0; c < 9; c++) {
            const int s = c % K3_STAGES;
            mbar_wait(full0 + 8 * s, (c / K3_STAGES) & 1);
            const uint32_t a_lo = ((sA + s * 16384 + wg * 8192) >> 4) | (1u << 16);
            const uint32_t b_lo = ((sW + c * 1024) >> 4) | (8u << 16);
            WG_FENCE();
            #pragma unroll
            for (int kk = 0; kk < 4; kk++) wgmma_n72_ss(aa, mkdesc(a_lo + kk * 2, hiA), mkdesc(b_lo + kk * 16, hiB), 1);
            WG_COMMIT();
            WG_WAIT(1);
            if (c > 0 && (threadIdx.x & 127) == 0) mbar_arrive(empty0 + 8 * ((c - 1) % K3_STAGES));
        }
        #pragma unroll 1
        for (int c = 9; c < 18; c++) {
            const int s = c % K3_STAGES;
            mbar_wait(full0 + 8 * s, (c / K3_STAGES) & 1);
            const uint32_t a_lo = ((sA + s * 16384 + wg * 8192) >> 4) | (1u << 16);
            const uint32_t b_lo = ((sW + K3_WBYTES + (c - 9) * 1024) >> 4) | (8u << 16);
            WG_FENCE();
            #pragma unroll
            for (int kk = 0; kk < 4; kk++) wgmma_n72_ss(ab, mkdesc(a_lo + kk * 2, hiA), mkdesc(b_lo + kk * 16, hiB), 1);
            WG_COMMIT();
            WG_WAIT(1);
            if ((threadIdx.x & 127) == 0) mbar_arrive(empty0 + 8 * ((c - 1) % K3_STAGES));
        }
        WG_WAIT(0);
        fence_regs(aa); fence_regs(ab);
        const int r0 = m0 + wg * 64 + warp * 16 + g;
        const float g0 = g_gate[r0], g1 = g_gate[r0 + 8];
        const float h0 = bfr(1.0f - g0), h1 = bfr(1.0f - g1);
        uint32_t* o0 = (uint32_t*)(out + (size_t)r0 * DM + n0) + t;
        uint32_t* o1 = (uint32_t*)(out + (size_t)(r0 + 8) * DM + n0) + t;
        #pragma unroll
        for (int j = 0; j < 9; j++) {
            float v0 = bfr(g0 * bfr(aa[4 * j])) + bfr(h0 * bfr(ab[4 * j]));
            float v1 = bfr(g0 * bfr(aa[4 * j + 1])) + bfr(h0 * bfr(ab[4 * j + 1]));
            float v2 = bfr(g1 * bfr(aa[4 * j + 2])) + bfr(h1 * bfr(ab[4 * j + 2]));
            float v3 = bfr(g1 * bfr(aa[4 * j + 3])) + bfr(h1 * bfr(ab[4 * j + 3]));
            o0[4 * j] = pack_bf16(v0, v1);
            o1[4 * j] = pack_bf16(v2, v3);
        }
    }
}

typedef CUresult (*EncodeFn)(CUtensorMap*, CUtensorMapDataType, cuuint32_t, void*, const cuuint64_t*, const cuuint64_t*,
                             const cuuint32_t*, const cuuint32_t*, CUtensorMapInterleave, CUtensorMapSwizzle,
                             CUtensorMapL2promotion, CUtensorMapFloatOOBfill);

static void make_map(EncodeFn enc, CUtensorMap* m, const void* base, uint64_t inner, uint64_t outer, uint32_t box_in, uint32_t box_out, CUtensorMapSwizzle sw) {
    cuuint64_t dims[2] = {inner, outer};
    cuuint64_t strides[1] = {inner * 2};
    cuuint32_t box[2] = {box_in, box_out};
    cuuint32_t es[2] = {1, 1};
    enc(m, CU_TENSOR_MAP_DATA_TYPE_BFLOAT16, 2, (void*)base, dims, strides, box, es, CU_TENSOR_MAP_INTERLEAVE_NONE, sw,
        CU_TENSOR_MAP_L2_PROMOTION_L2_256B, CU_TENSOR_MAP_FLOAT_OOB_FILL_NONE);
}

extern "C" void kernel_launch(void* const* d_in, const int* in_sizes, int n_in, void* d_out, int out_size) {
    const __nv_bfloat16* x = (const __nv_bfloat16*)d_in[0];
    const __nv_bfloat16* wA = (const __nv_bfloat16*)d_in[1];
    const __nv_bfloat16* woA = (const __nv_bfloat16*)d_in[2];
    const __nv_bfloat16* wB = (const __nv_bfloat16*)d_in[4];
    const __nv_bfloat16* woB = (const __nv_bfloat16*)d_in[5];
    const __nv_bfloat16* gw = (const __nv_bfloat16*)d_in[6];
    __nv_bfloat16* out = (__nv_bfloat16*)d_out;

    static EncodeFn enc = nullptr;
    static void *pOA = nullptr, *pOB = nullptr;
    if (!enc) {
        void* fn = nullptr; cudaDriverEntryPointQueryResult st;
        cudaGetDriverEntryPoint("cuTensorMapEncodeTiled", &fn, cudaEnableDefault, &st);
        enc = (EncodeFn)fn;
        cudaGetSymbolAddress(&pOA, g_OA);
        cudaGetSymbolAddress(&pOB, g_OB);
        cudaFuncSetAttribute(qkv_kernel, cudaFuncAttributeMaxDynamicSharedMemorySize, K1_SMEM);
        cudaFuncSetAttribute(attn_kernel, cudaFuncAttributeMaxDynamicSharedMemorySize, K2_SMEM);
        cudaFuncSetAttribute(out_kernel, cudaFuncAttributeMaxDynamicSharedMemorySize, K3_SMEM);
    }
    CUtensorMap mX, mWA, mWA2, mWB, mWB2, mOA, mOB;
    make_map(enc, &mX, x, DM, S_LEN, 64, 256, CU_TENSOR_MAP_SWIZZLE_128B);
    make_map(enc, &mWA, wA, 3 * DM, DM, 64, 64, CU_TENSOR_MAP_SWIZZLE_128B);
    make_map(enc, &mWA2, wA, 3 * DM, DM, 32, 64, CU_TENSOR_MAP_SWIZZLE_64B);
    make_map(enc, &mWB, wB, 3 * DM, DM, 64, 64, CU_TENSOR_MAP_SWIZZLE_128B);
    make_map(enc, &mWB2, wB, 3 * DM, DM, 32, 64, CU_TENSOR_MAP_SWIZZLE_64B);
    make_map(enc, &mOA, pOA, DM, S_LEN, 64, 128, CU_TENSOR_MAP_SWIZZLE_128B);
    make_map(enc, &mOB, pOB, DM, S_LEN, 64, 128, CU_TENSOR_MAP_SWIZZLE_128B);

    cudaStream_t stream = cudaStreamPerThread;
    cudaLaunchAttribute at[1];
    at[0].id = cudaLaunchAttributeProgrammaticStreamSerialization;
    at[0].val.programmaticStreamSerializationAllowed = 1;

    qkv_kernel<<<128, 256, K1_SMEM, stream>>>(mX, mWA, mWA2, mWB, mWB2);

    cudaLaunchConfig_t c2 = {};
    c2.gridDim = dim3(132); c2.blockDim = dim3(512); c2.dynamicSmemBytes = K2_SMEM; c2.stream = stream; c2.attrs = at; c2.numAttrs = 1;
    cudaLaunchKernelEx(&c2, attn_kernel, x, gw);

    cudaLaunchConfig_t c3 = {};
    c3.gridDim = dim3(128); c3.blockDim = dim3(288); c3.dynamicSmemBytes = K3_SMEM; c3.stream = stream; c3.attrs = at; c3.numAttrs = 1;
    cudaLaunchKernelEx(&c3, out_kernel, mOA, mOB, woA, woB, out);
}
```

```cpp
#include <cuda_runtime.h>
#include <cuda_bf16.h>
#include <cuda.h>
#include <stdint.h>

#define S_LEN 2048
#define DM 576
#define NH 32
#define DH 18
#define HEAD_ELEMS 49152
#define HEAD_BYTES 98304

#define POLY_BLK 0xAAAA

__device__ __align__(1024) __nv_bfloat16 g_T[6 * NH * HEAD_ELEMS];
__device__ float g_kmax[8][NH];
__device__ __align__(1024) __nv_bfloat16 g_O[2 * S_LEN * DM];
__device__ float g_gate[S_LEN];
__device__ __align__(128) __nv_bfloat16 g_kv[NH * 768];
__device__ int g_kvflag[NH];
__device__ __align__(1024) __nv_bfloat16 g_Wt[8 * 2 * 4 * 10368];

#define TSTAMP(k, i)
#define WG_FENCE() asm volatile("wgmma.fence.sync.aligned;\n" ::: "memory")
#define WG_COMMIT() asm volatile("wgmma.commit_group.sync.aligned;\n" ::: "memory")
#define WG_WAIT(n) asm volatile("wgmma.wait_group.sync.aligned %0;\n" :: "n"(n) : "memory")

__device__ __forceinline__ uint64_t mkdesc(uint32_t lo, uint32_t hi) {
    uint64_t d; asm("mov.b64 %0, {%1, %2};" : "=l"(d) : "r"(lo), "r"(hi)); return d;
}
__device__ __forceinline__ uint32_t smem_u32(const void* p) { return (uint32_t)__cvta_generic_to_shared(p); }
__device__ __forceinline__ void mbar_init(uint32_t bar, uint32_t cnt) { asm volatile("mbarrier.init.shared::cta.b64 [%0], %1;" :: "r"(bar), "r"(cnt)); }
__device__ __forceinline__ void mbar_expect_tx(uint32_t bar, uint32_t bytes) { asm volatile("mbarrier.arrive.expect_tx.shared::cta.b64 _, [%0], %1;" :: "r"(bar), "r"(bytes) : "memory"); }
__device__ __forceinline__ void mbar_arrive(uint32_t bar) { asm volatile("mbarrier.arrive.shared::cta.b64 _, [%0];" :: "r"(bar) : "memory"); }
__device__ __forceinline__ void mbar_wait(uint32_t bar, uint32_t parity) {
    asm volatile("{\n.reg .pred p;\nWAIT_%=:\nmbarrier.try_wait.parity.shared::cta.b64 p, [%0], %1;\n@p bra DONE_%=;\nbra WAIT_%=;\nDONE_%=:\n}\n" :: "r"(bar), "r"(parity) : "memory");
}
__device__ __forceinline__ void mbar_wait_w(uint32_t bar, uint32_t parity) { __syncwarp(); mbar_wait(bar, parity); }
__device__ __forceinline__ void bulk_g2s(uint32_t dst, const void* src, uint32_t bytes, uint32_t bar) {
    asm volatile("cp.async.bulk.shared::cluster.global.mbarrier::complete_tx::bytes [%0], [%1], %2, [%3];" :: "r"(dst), "l"(src), "r"(bytes), "r"(bar) : "memory");
}
__device__ __forceinline__ void tma_2d(uint32_t dst, const CUtensorMap* map, int c0, int c1, uint32_t bar) {
    asm volatile("cp.async.bulk.tensor.2d.shared::cluster.global.mbarrier::complete_tx::bytes [%0], [%1, {%3, %4}], [%2];"
                 :: "r"(dst), "l"((uint64_t)map), "r"(bar), "r"(c0), "r"(c1) : "memory");
}
__device__ __forceinline__ void tma_3d(uint32_t dst, const CUtensorMap* map, int c0, int c1, int c2, uint32_t bar) {
    asm volatile("cp.async.bulk.tensor.3d.shared::cluster.global.mbarrier::complete_tx::bytes [%0], [%1, {%3, %4, %5}], [%2];"
                 :: "r"(dst), "l"((uint64_t)map), "r"(bar), "r"(c0), "r"(c1), "r"(c2) : "memory");
}
__device__ __forceinline__ void named_bar(int id, int n) { asm volatile("bar.sync %0, %1;" :: "r"(id), "r"(n) : "memory"); }
__device__ __forceinline__ void fence_async() { asm volatile("fence.proxy.async.shared::cta;" ::: "memory"); }
__device__ __forceinline__ void pdl_wait() { asm volatile("griddepcontrol.wait;" ::: "memory"); }
__device__ __forceinline__ void pdl_launch() { asm volatile("griddepcontrol.launch_dependents;" ::: "memory"); }

__device__ __forceinline__ float ex2f(float x) { float y; asm("ex2.approx.ftz.f32 %0, %1;" : "=f"(y) : "f"(x)); return y; }
__device__ __forceinline__ uint32_t pack_bf16(float lo, float hi) { uint32_t r; asm("cvt.rn.bf16x2.f32 %0, %1, %2;" : "=r"(r) : "f"(hi), "f"(lo)); return r; }
__device__ __forceinline__ float bf_lo(uint32_t v) { return __uint_as_float(v << 16); }
__device__ __forceinline__ float bf_hi(uint32_t v) { return __uint_as_float(v & 0xFFFF0000u); }
__device__ __forceinline__ float bfr(float x) { return __uint_as_float(pack_bf16(0.f, x) & 0xFFFF0000u); }

#define ACC4(a, o) "+f"(a[o]), "+f"(a[o + 1]), "+f"(a[o + 2]), "+f"(a[o + 3])
#define ACC12(a, o) ACC4(a, o), ACC4(a, o + 4), ACC4(a, o + 8)
#define ACC16(a, o) ACC4(a, o), ACC4(a, o + 4), ACC4(a, o + 8), ACC4(a, o + 12)
#define ACC32(a, o) ACC16(a, o), ACC16(a, o + 16)

__device__ __forceinline__ void wgmma_n24_rs(float (&d)[12], uint32_t a0, uint32_t a1, uint32_t a2, uint32_t a3, uint64_t bdesc) {
    asm volatile("{\n.reg .pred p;\nsetp.ne.b32 p, 1, 0;\n"
        "wgmma.mma_async.sync.aligned.m64n24k16.f32.bf16.bf16 "
        "{%0,%1,%2,%3,%4,%5,%6,%7,%8,%9,%10,%11}, {%12,%13,%14,%15}, %16, p, 1, 1, 1;\n}\n"
        : ACC12(d, 0) : "r"(a0), "r"(a1), "r"(a2), "r"(a3), "l"(bdesc));
}
template<int TA, int TB>
__device__ __forceinline__ void wgmma_n24_ss(float (&d)[12], uint64_t adesc, uint64_t bdesc, int acc) {
    asm volatile("{\n.reg .pred p;\nsetp.ne.b32 p, %14, 0;\n"
        "wgmma.mma_async.sync.aligned.m64n24k16.f32.bf16.bf16 "
        "{%0,%1,%2,%3,%4,%5,%6,%7,%8,%9,%10,%11}, %12, %13, p, 1, 1, %15, %16;\n}\n"
        : ACC12(d, 0) : "l"(adesc), "l"(bdesc), "r"(acc), "n"(TA), "n"(TB));
}
template<int ACC>
__device__ __forceinline__ void wgmma_n128_rs(float (&d)[64], uint32_t a0, uint32_t a1, uint32_t a2, uint32_t a3, uint64_t bdesc) {
    asm volatile("{\n.reg .pred p;\nsetp.ne.b32 p, %69, 0;\n"
        "wgmma.mma_async.sync.aligned.m64n128k16.f32.bf16.bf16 "
        "{%0,%1,%2,%3,%4,%5,%6,%7,%8,%9,%10,%11,%12,%13,%14,%15,%16,%17,%18,%19,%20,%21,%22,%23,%24,%25,%26,%27,%28,%29,%30,%31,"
        "%32,%33,%34,%35,%36,%37,%38,%39,%40,%41,%42,%43,%44,%45,%46,%47,%48,%49,%50,%51,%52,%53,%54,%55,%56,%57,%58,%59,%60,%61,%62,%63}, {%64,%65,%66,%67}, %68, p, 1, 1, 0;\n}\n"
        : ACC32(d, 0), ACC32(d, 32) : "r"(a0), "r"(a1), "r"(a2), "r"(a3), "l"(bdesc), "n"(ACC));
}
__device__ __forceinline__ void wgmma_n192_ss(float (&d)[96], uint64_t adesc, uint64_t bdesc, int acc) {
    asm volatile("{\n.reg .pred p;\nsetp.ne.b32 p, %98, 0;\n"
        "wgmma.mma_async.sync.aligned.m64n192k16.f32.bf16.bf16 "
        "{%0,%1,%2,%3,%4,%5,%6,%7,%8,%9,%10,%11,%12,%13,%14,%15,%16,%17,%18,%19,%20,%21,%22,%23,%24,%25,%26,%27,%28,%29,%30,%31,"
        "%32,%33,%34,%35,%36,%37,%38,%39,%40,%41,%42,%43,%44,%45,%46,%47,%48,%49,%50,%51,%52,%53,%54,%55,%56,%57,%58,%59,%60,%61,%62,%63,"
        "%64,%65,%66,%67,%68,%69,%70,%71,%72,%73,%74,%75,%76,%77,%78,%79,%80,%81,%82,%83,%84,%85,%86,%87,%88,%89,%90,%91,%92,%93,%94,%95}, %96, %97, p, 1, 1, 0, 1;\n}\n"
        : ACC32(d, 0), ACC32(d, 32), ACC32(d, 64) : "l"(adesc), "l"(bdesc), "r"(acc));
}
__device__ __forceinline__ void wgmma_n216_ss(float (&d)[108], uint64_t adesc, uint64_t bdesc) {
    asm volatile("{\n.reg .pred p;\nsetp.ne.b32 p, 1, 0;\n"
        "wgmma.mma_async.sync.aligned.m64n216k16.f32.bf16.bf16 "
        "{%0,%1,%2,%3,%4,%5,%6,%7,%8,%9,%10,%11,%12,%13,%14,%15,%16,%17,%18,%19,%20,%21,%22,%23,%24,%25,%26,%27,%28,%29,%30,%31,%32,%33,%34,%35,%36,%37,%38,%39,%40,%41,%42,%43,%44,%45,%46,%47,%48,%49,%50,%51,%52,%53,%54,%55,%56,%57,%58,%59,%60,%61,%62,%63,%64,%65,%66,%67,%68,%69,%70,%71,%72,%73,%74,%75,%76,%77,%78,%79,%80,%81,%82,%83,%84,%85,%86,%87,%88,%89,%90,%91,%92,%93,%94,%95,%96,%97,%98,%99,%100,%101,%102,%103,%104,%105,%106,%107}, %108, %109, p, 1, 1, 0, 1;\n}\n"
        : ACC32(d, 0), ACC32(d, 32), ACC32(d, 64), ACC12(d, 96) : "l"(adesc), "l"(bdesc));
}
__device__ __forceinline__ void wgmma_n72_ss(float (&d)[36], uint64_t adesc, uint64_t bdesc, int acc) {
    asm volatile("{\n.reg .pred p;\nsetp.ne.b32 p, %38, 0;\n"
        "wgmma.mma_async.sync.aligned.m64n72k16.f32.bf16.bf16 "
        "{%0,%1,%2,%3,%4,%5,%6,%7,%8,%9,%10,%11,%12,%13,%14,%15,%16,%17,%18,%19,%20,%21,%22,%23,%24,%25,%26,%27,%28,%29,%30,%31,"
        "%32,%33,%34,%35}, %36, %37, p, 1, 1, 0, 1;\n}\n"
        : ACC32(d, 0), ACC4(d, 32) : "l"(adesc), "l"(bdesc), "r"(acc));
}
template<int N> __device__ __forceinline__ void fence_regs(float (&d)[N]) {
    #pragma unroll
    for (int i = 0; i < N; i++) asm volatile("" : "+f"(d[i]) :: "memory");
}

#define K1_STAGES 3
#define K1_STAGE_BYTES 61440
#define K1_SMEM (K1_STAGES * K1_STAGE_BYTES + 1024)
#define STG_PITCH 436

__device__ __forceinline__ uint32_t hadd2_bf16(uint32_t a, uint32_t b) { uint32_t r; asm("add.rn.bf16x2 %0, %1, %2;" : "=r"(r) : "r"(a), "r"(b)); return r; }
__device__ __forceinline__ uint32_t phi_pair(uint32_t w) {
    const uint32_t p1 = hadd2_bf16(w, 0x3F803F80u);
    const uint32_t pe = pack_bf16(ex2f(bf_lo(w) * 1.4426950408889634f), ex2f(bf_hi(w) * 1.4426950408889634f));
    uint32_t m; asm("prmt.b32 %0, %1, 0, 0xBB99;" : "=r"(m) : "r"(w));
    const uint32_t r = (pe & m) | (p1 & ~m);
    return pack_bf16(bf_lo(r) + 1e-6f, bf_hi(r) + 1e-6f);
}
__device__ __forceinline__ uint32_t qscale_pair(uint32_t w) {
    const float qs = 0.23570226039551584f * 1.4426950408889634f;
    return pack_bf16(bf_lo(w) * qs, bf_hi(w) * qs);
}
__device__ __forceinline__ void sts32(uint32_t addr, uint32_t v) { asm volatile("st.shared.b32 [%0], %1;" :: "r"(addr), "r"(v) : "memory"); }

__global__ void __launch_bounds__(256, 1)
qkv_kernel(const __grid_constant__ CUtensorMap mapX, const __grid_constant__ CUtensorMap mapWA, const __grid_constant__ CUtensorMap mapWA2,
           const __grid_constant__ CUtensorMap mapWB, const __grid_constant__ CUtensorMap mapWB2) {
    extern __shared__ unsigned char smem_raw[];
    __shared__ __align__(8) uint64_t bars[2 * K1_STAGES];
    __shared__ uint32_t s_nmax[12];
    const uint32_t sbase = (smem_u32(smem_raw) + 1023u) & ~1023u;
    unsigned char* stg = smem_raw + (sbase - smem_u32(smem_raw));
    const uint32_t full0 = smem_u32(bars), empty0 = full0 + 8 * K1_STAGES;
    const int mt = blockIdx.x >> 4, nt = blockIdx.x & 15;
    const int branch = nt >> 3, n0 = (nt & 7) * 216, m0 = mt * 256;
    const int wg = threadIdx.x >> 7;
    const int warp = (threadIdx.x >> 5) & 3, lane = threadIdx.x & 31, g = lane >> 2, t = lane & 3;
    TSTAMP(0, 0);
    const CUtensorMap* w1 = branch ? &mapWB : &mapWA;
    const CUtensorMap* w2 = branch ? &mapWB2 : &mapWA2;
    auto issue = [&](int kt) {
        const int s = kt % K1_STAGES;
        const uint32_t st = sbase + s * K1_STAGE_BYTES, fb = full0 + 8 * s;
        mbar_expect_tx(fb, K1_STAGE_BYTES);
        tma_2d(st, &mapX, kt * 64, m0, fb);
        tma_2d(st + 32768, w1, n0, kt * 64, fb);
        tma_2d(st + 32768 + 8192, w1, n0 + 64, kt * 64, fb);
        tma_2d(st + 32768 + 16384, w1, n0 + 128, kt * 64, fb);
        tma_2d(st + 32768 + 24576, w2, n0 + 192, kt * 64, fb);
    };
    if (threadIdx.x == 0) {
        for (int i = 0; i < K1_STAGES; i++) { mbar_init(full0 + 8 * i, 1); mbar_init(empty0 + 8 * i, 2); }
        asm volatile("fence.mbarrier_init.release.cluster;" ::: "memory");
        issue(0); issue(1); issue(2);
    }
    if (threadIdx.x < 12) s_nmax[threadIdx.x] = 0;
    if (blockIdx.x == 0 && threadIdx.x >= 32 && threadIdx.x < 64) g_kvflag[threadIdx.x - 32] = 0;
    __syncthreads();
    pdl_launch();
    const uint32_t hiA = 64u | 0x40000000u;
    const uint32_t hiB = 64u | 0x40000000u;
    const uint32_t hiB2 = 32u | 0x80000000u;
    float acc0[96], acc1[96], acd0[12], acd1[12];
    #pragma unroll
    for (int i = 0; i < 96; i++) { acc0[i] = 0.f; acc1[i] = 0.f; }
    #pragma unroll
    for (int i = 0; i < 12; i++) { acd0[i] = 0.f; acd1[i] = 0.f; }
    fence_regs(acc0); fence_regs(acc1); fence_regs(acd0); fence_regs(acd1);
    #pragma unroll 1
    for (int kt = 0; kt < 9; kt++) {
        const int s = kt % K1_STAGES;
        mbar_wait_w(full0 + 8 * s, (kt / K1_STAGES) & 1);
        const uint32_t st = sbase + s * K1_STAGE_BYTES;
        const uint32_t a_lo = ((st + wg * 16384) >> 4) | (1u << 16);
        const uint32_t b_lo = ((st + 32768) >> 4) | (512u << 16);
        const uint32_t b2_lo = ((st + 32768 + 24576) >> 4) | (1u << 16);
        WG_FENCE();
        #pragma unroll
        for (int kk = 0; kk < 4; kk++) {
            wgmma_n192_ss(acc0, mkdesc(a_lo + kk * 2, hiA), mkdesc(b_lo + kk * 128, hiB), 1);
            wgmma_n24_ss<0, 1>(acd0, mkdesc(a_lo + kk * 2, hiA), mkdesc(b2_lo + kk * 64, hiB2), 1);
            wgmma_n192_ss(acc1, mkdesc(a_lo + 512 + kk * 2, hiA), mkdesc(b_lo + kk * 128, hiB), 1);
            wgmma_n24_ss<0, 1>(acd1, mkdesc(a_lo + 512 + kk * 2, hiA), mkdesc(b2_lo + kk * 64, hiB2), 1);
        }
        WG_COMMIT();
        WG_WAIT(1);
        if (kt > 0) {
            const int sp = (kt - 1) % K1_STAGES;
            if ((threadIdx.x & 127) == 0) mbar_arrive(empty0 + 8 * sp);
            if (threadIdx.x < 32 && kt + 2 < 9) {
                mbar_wait_w(empty0 + 8 * sp, ((kt - 1) / K1_STAGES) & 1);
                if (threadIdx.x == 0) issue(kt + 2);
            }
            __syncwarp();
        }
    }
    WG_WAIT(0);
    fence_regs(acc0); fence_regs(acc1); fence_regs(acd0); fence_regs(acd1);
    TSTAMP(0, 1);
    __syncthreads();
    {
        uint32_t off9[9];
        #pragma unroll
        for (int jj = 0; jj < 9; jj++) {
            const int c = 8 * jj + 2 * t, hh = c / 18, d = c - hh * 18;
            off9[jj] = hh * 12288 + (d >> 3) * 128 + (d & 7) * 2;
        }
        const uint32_t base = sbase + (wg * 16 + warp * 2) * 384 + g * 16;
        const int k0 = branch * 3 + n0 / 576, k1 = branch * 3 + (n0 + 72) / 576, k2 = branch * 3 + (n0 + 144) / 576;
        const int row = threadIdx.x;
        const uint32_t pmagic = ((POLY_BLK >> ((row & 127) >> 3)) & 1) ? 0x46013F80u : 0x3F803F80u;
        const uint32_t pa = sbase + (row >> 3) * 384 + 256 + (row & 7) * 16 + 4;
        #pragma unroll
        for (int hh = 0; hh < 12; hh++) {
            const int kind = hh < 4 ? k0 : hh < 8 ? k1 : k2;
            sts32(pa + hh * 12288, kind == 4 ? pmagic : (kind == 2 || kind == 5) ? 0x00003F80u : 0u);
            asm volatile("st.shared.v2.b32 [%0], {%1, %1};" :: "r"(pa + hh * 12288 + 4), "r"(0u) : "memory");
        }
        auto flush = [&](int grp) {
            fence_async();
            __syncthreads();
            if (threadIdx.x < 4) {
                const int hh = grp * 4 + threadIdx.x, col0 = n0 + hh * 18;
                const int type = col0 / 576, head = (col0 % 576) / 18, kind = branch * 3 + type;
                const size_t hb = (kind == 1 || kind == 2) ? (size_t)(NH + 2 * head) * HEAD_ELEMS + mt * 12288 + (kind - 1) * 6144
                                                           : (size_t)(kind * NH + head) * HEAD_ELEMS + mt * 6144;
                asm volatile("cp.async.bulk.global.shared::cta.bulk_group [%0], [%1], %2;" :: "l"(g_T + hb), "r"(sbase + hh * 12288), "r"(12288) : "memory");
                asm volatile("cp.async.bulk.commit_group;" ::: "memory");
            }
        };
        #pragma unroll
        for (int j = 0; j < 27; j++) {
            const uint32_t a = base + (j / 9) * 49152 + off9[j % 9];
            if (j < 24) {
                sts32(a, pack_bf16(acc0[(4 * j) % 96], acc0[(4 * j + 1) % 96]));
                sts32(a + 384, pack_bf16(acc0[(4 * j + 2) % 96], acc0[(4 * j + 3) % 96]));
                sts32(a + 3072, pack_bf16(acc1[(4 * j) % 96], acc1[(4 * j + 1) % 96]));
                sts32(a + 3456, pack_bf16(acc1[(4 * j + 2) % 96], acc1[(4 * j + 3) % 96]));
            } else {
                sts32(a, pack_bf16(acd0[(4 * j) % 12], acd0[(4 * j + 1) % 12]));
                sts32(a + 384, pack_bf16(acd0[(4 * j + 2) % 12], acd0[(4 * j + 3) % 12]));
                sts32(a + 3072, pack_bf16(acd1[(4 * j) % 12], acd1[(4 * j + 1) % 12]));
                sts32(a + 3456, pack_bf16(acd1[(4 * j + 2) % 12], acd1[(4 * j + 3) % 12]));
            }
        }
        __syncthreads();
        #pragma unroll 1
        for (int grp = 0; grp < 3; grp++) {
            const int kind = grp == 0 ? k0 : grp == 1 ? k1 : k2;
            if (kind <= 1 || kind == 3) {
                unsigned char* rp = stg + grp * 49152 + (row >> 3) * 384 + (row & 7) * 16;
                #pragma unroll 2
                for (int hq = 0; hq < 4; hq++) {
                    uint4 v0 = *(uint4*)(rp + hq * 12288), v1 = *(uint4*)(rp + hq * 12288 + 128);
                    uint32_t v2 = *(uint32_t*)(rp + hq * 12288 + 256);
                    if (kind == 3) {
                        v0.x = qscale_pair(v0.x); v0.y = qscale_pair(v0.y); v0.z = qscale_pair(v0.z); v0.w = qscale_pair(v0.w);
                        v1.x = qscale_pair(v1.x); v1.y = qscale_pair(v1.y); v1.z = qscale_pair(v1.z); v1.w = qscale_pair(v1.w);
                        v2 = qscale_pair(v2);
                    } else {
                        v0.x = phi_pair(v0.x); v0.y = phi_pair(v0.y); v0.z = phi_pair(v0.z); v0.w = phi_pair(v0.w);
                        v1.x = phi_pair(v1.x); v1.y = phi_pair(v1.y); v1.z = phi_pair(v1.z); v1.w = phi_pair(v1.w);
                        v2 = phi_pair(v2);
                    }
                    *(uint4*)(rp + hq * 12288) = v0; *(uint4*)(rp + hq * 12288 + 128) = v1;
                    *(uint32_t*)(rp + hq * 12288 + 256) = v2;
                }
            }
            flush(grp);
        }
        TSTAMP(0, 3);
        #pragma unroll 1
        for (int grp = 0; grp < 3; grp++) {
            if ((grp == 0 ? k0 : grp == 1 ? k1 : k2) == 4) {
                #pragma unroll 2
                for (int hq = 0; hq < 4; hq++) {
                    const unsigned char* src = stg + (grp * 4 + hq) * 12288 + (row >> 3) * 384 + (row & 7) * 16;
                    const uint4 v0 = *(const uint4*)src, v1 = *(const uint4*)(src + 128);
                    const uint32_t w[9] = {v0.x, v0.y, v0.z, v0.w, v1.x, v1.y, v1.z, v1.w, *(const uint32_t*)(src + 256)};
                    float n2 = 0.f;
                    #pragma unroll
                    for (int i = 0; i < 9; i++) { const float a = bf_lo(w[i]), b = bf_hi(w[i]); n2 = fmaf(a, a, n2); n2 = fmaf(b, b, n2); }
                    uint32_t nb = __float_as_uint(n2);
                    if (!(n2 >= 0.f)) nb = 0x7F800000u;
                    nb = __reduce_max_sync(0xFFFFFFFFu, nb);
                    if (lane == 0) atomicMax(&s_nmax[grp * 4 + hq], nb);
                }
            }
        }
        __syncthreads();
        if (threadIdx.x < 12) {
            const int col0 = n0 + threadIdx.x * 18;
            if (branch == 1 && col0 / 576 == 1) g_kmax[mt][(col0 % 576) / 18] = __uint_as_float(s_nmax[threadIdx.x]);
            asm volatile("cp.async.bulk.wait_group 0;" ::: "memory");
        }
    }
    TSTAMP(0, 2);
}

__device__ __forceinline__ uint32_t hfma2(uint32_t a, uint32_t b, uint32_t c) { uint32_t r; asm("fma.rn.f16x2 %0, %1, %2, %3;" : "=r"(r) : "r"(a), "r"(b), "r"(c)); return r; }
__device__ __forceinline__ uint32_t and_or(uint32_t a, uint32_t m, uint32_t o) { uint32_t r; asm("lop3.b32 %0, %1, %2, %3, 0xEA;" : "=r"(r) : "r"(a), "r"(m), "r"(o)); return r; }
__device__ __forceinline__ uint32_t poly_ex2_pair(float t0, float t1) {
    const uint32_t u = __byte_perm(__float_as_uint(t0), __float_as_uint(t1), 0x5410);
    const uint32_t m = and_or(u, 0x03FF03FFu, 0x3C003C00u);
    uint32_t y = hfma2(m, 0x2CFE2CFEu, 0xA019A019u);
    y = hfma2(y, m, 0xB82EB82Eu);
    y = hfma2(y, m, 0x3FCF3FCFu);
    const uint32_t w = u + y + 0xC203C204u;
    return and_or(w >> 3, 0x1FFF1FFFu, 0x20002000u);
}

template<int B0, int NB>
__device__ __forceinline__ void softmax_blocks(float (&s)[64], uint32_t (&p)[32]) {
    #pragma unroll
    for (int i = B0 * 4; i < (B0 + NB) * 4; i++) asm volatile("" : "+f"(s[i]) :: "memory");
    #pragma unroll
    for (int b = B0; b < B0 + NB; b++) {
        if ((POLY_BLK >> b) & 1) {
            p[2 * b + 0] = poly_ex2_pair(s[4 * b], s[4 * b + 1]);
            p[2 * b + 1] = poly_ex2_pair(s[4 * b + 2], s[4 * b + 3]);
        } else {
            p[2 * b + 0] = pack_bf16(ex2f(s[4 * b]), ex2f(s[4 * b + 1]));
            p[2 * b + 1] = pack_bf16(ex2f(s[4 * b + 2]), ex2f(s[4 * b + 3]));
        }
    }
}

__device__ __forceinline__ void store_o(int branch, int row0, int h, int t, const float (&o)[12], float r0, float r1) {
    uint32_t* p = (uint32_t*)g_O + ((((branch * 16 + (row0 >> 7)) * 8 + (h >> 2)) * 16 + ((row0 >> 3) & 15)) * 72 + (row0 & 7)) * 4;
    uint32_t* q = p + (h & 3) * 64 + t;
    q[0] = pack_bf16(o[0] * r0, o[1] * r0); q[288] = pack_bf16(o[2] * r1, o[3] * r1);
    q[32] = pack_bf16(o[4] * r0, o[5] * r0); q[288 + 32] = pack_bf16(o[6] * r1, o[7] * r1);
    if (t == 0) { p[256 + (h & 3)] = pack_bf16(o[8] * r0, o[9] * r0); p[288 + 256 + (h & 3)] = pack_bf16(o[10] * r1, o[11] * r1); }
}

#define K2_SMEM (2 * HEAD_BYTES + 24576 + 1536 + 1024)

__global__ void __launch_bounds__(512, 1)
attn_kernel(const __nv_bfloat16* __restrict__ x, const __nv_bfloat16* __restrict__ gate_w,
            const __nv_bfloat16* __restrict__ woA, const __nv_bfloat16* __restrict__ woB) {
    extern __shared__ unsigned char smem_raw[];
    __shared__ __align__(8) uint64_t bars[16];
    const uint32_t sK = (smem_u32(smem_raw) + 1023u) & ~1023u;
    const uint32_t sV = sK + HEAD_BYTES;
    unsigned char* sgen = smem_raw + (sK - smem_u32(smem_raw));
    TSTAMP(1, 0);
    const uint32_t bar0 = smem_u32(bars);
    const int wg = threadIdx.x >> 7, warp = (threadIdx.x >> 5) & 3, lane = threadIdx.x & 31, g = lane >> 2, t = lane & 3;
    if (threadIdx.x == 0) {
        for (int i = 0; i < 10; i++) mbar_init(bar0 + 8 * i, 1);
        asm volatile("fence.mbarrier_init.release.cluster;" ::: "memory");
    }
    __syncthreads();
    pdl_launch();
    const uint32_t kd0 = (sK >> 4) | (8u << 16);
    const uint32_t kd1 = ((sK + 256) >> 4);
    const uint32_t khi = 24;
    const uint32_t vd0 = (sV >> 4) | (24u << 16);
    const uint32_t vhi = 8;

    if (blockIdx.x < 4) {
        const int hb = blockIdx.x * 8 + wg * 2;
        const int tid = threadIdx.x & 127;
        {
            if (threadIdx.x < 8) asm volatile("cp.async.bulk.prefetch.L2.global [%0], %1;" :: "l"((const char*)((blockIdx.x & 1) ? woB : woA) + ((blockIdx.x >> 1) * 8 + threadIdx.x) * 41472), "r"(41472) : "memory");
            uint32_t gv[9];
            #pragma unroll
            for (int i = 0; i < 9; i++) gv[i] = ((const uint32_t*)gate_w)[lane + 32 * i];
            #pragma unroll 1
            for (int r = blockIdx.x * 512 + (threadIdx.x >> 5) * 8; r < blockIdx.x * 512 + 512; r += 128) {
                uint32_t xv[8][9];
                #pragma unroll
                for (int q = 0; q < 8; q++) {
                    #pragma unroll
                    for (int i = 0; i < 9; i++) xv[q][i] = ((const uint32_t*)(x + (size_t)(r + q) * DM))[lane + 32 * i];
                }
                float sum[8];
                #pragma unroll
                for (int q = 0; q < 8; q++) {
                    sum[q] = 0.f;
                    #pragma unroll
                    for (int i = 0; i < 9; i++) sum[q] += bfr(bf_lo(xv[q][i]) * bf_lo(gv[i])) + bfr(bf_hi(xv[q][i]) * bf_hi(gv[i]));
                }
                #pragma unroll
                for (int o = 16; o > 0; o >>= 1) {
                    #pragma unroll
                    for (int q = 0; q < 8; q++) sum[q] += __shfl_xor_sync(~0u, sum[q], o);
                }
                float z = sum[0];
                #pragma unroll
                for (int q = 1; q < 8; q++) z = lane == q ? sum[q] : z;
                if (lane < 8) g_gate[r + lane] = bfr(1.0f / (1.0f + __expf(-bfr(z))));
            }
        }
        TSTAMP(1, 3);
        pdl_wait();
        TSTAMP(1, 1);
        const uint32_t slot0 = sK + wg * 49152, fb0 = bar0 + wg * 16;
        auto issue = [&](int c) {
            mbar_expect_tx(fb0 + 8 * (c & 1), 24576);
            bulk_g2s(slot0 + (c & 1) * 24576, (const char*)(g_T + (size_t)(NH + 2 * hb) * HEAD_ELEMS) + (size_t)c * 24576, 24576, fb0 + 8 * (c & 1));
        };
        if (tid == 0) { issue(0); issue(1); }
        #pragma unroll 1
        for (int hi = 0; hi < 2; hi++) {
            float d1[4][12];
            #pragma unroll
            for (int k = 0; k < 4; k++) {
                #pragma unroll
                for (int i = 0; i < 12; i++) d1[k][i] = 0.f;
                fence_regs(d1[k]);
            }
            #pragma unroll 1
            for (int cc = 0; cc < 8; cc++) {
                const int c = hi * 8 + cc;
                mbar_wait_w(fb0 + 8 * (c & 1), (c >> 1) & 1);
                const uint32_t base = ((slot0 + (c & 1) * 24576) >> 4) | (24u << 16);
                WG_FENCE();
                #pragma unroll
                for (int ks = 0; ks < 16; ks++)
                    wgmma_n24_ss<1, 1>(d1[ks & 3], mkdesc(base + ks * 48, 8u), mkdesc(base + 768 + ks * 48, vhi), 1);
                WG_COMMIT();
                WG_WAIT(0);
                named_bar(1 + wg, 128);
                if (tid == 0 && c + 2 < 16) issue(c + 2);
            }
            #pragma unroll
            for (int k = 0; k < 4; k++) fence_regs(d1[k]);
            #pragma unroll
            for (int i = 0; i < 12; i++) d1[0][i] = (d1[0][i] + d1[1][i]) + (d1[2][i] + d1[3][i]);
            if (warp < 2) {
                const int d = warp * 16 + g;
                uint32_t* kp = (uint32_t*)(g_kv + (hb + hi) * 768 + (d >> 3) * 192 + (d & 7) * 8 + 2 * t);
                #pragma unroll
                for (int j = 0; j < 3; j++) {
                    kp[32 * j] = d < 18 ? pack_bf16(d1[0][4 * j], d1[0][4 * j + 1]) : 0u;
                    kp[96 + 32 * j] = warp == 0 ? pack_bf16(d1[0][4 * j + 2], d1[0][4 * j + 3]) : 0u;
                }
                __threadfence();
            }
            named_bar(1 + wg, 128);
            if (tid == 0) asm volatile("st.release.gpu.global.b32 [%0], %1;" :: "l"(g_kvflag + hb + hi), "r"(1) : "memory");
        }
        TSTAMP(1, 4);
        TSTAMP(1, 2);
        return;
    }
    const int cta = blockIdx.x - 4;

    {
        uint4 wv[2];
        #pragma unroll
        for (int q = 0; q < 2; q++) {
            const int id = cta * 648 + threadIdx.x + q * 512;
            if (threadIdx.x + q * 512 < 648) wv[q] = *(const uint4*)((id >= 41472 ? woB - 41472 * 8 : woA) + (size_t)id * 8);
        }
        #pragma unroll
        for (int q = 0; q < 2; q++) {
            const int id = cta * 648 + threadIdx.x + q * 512;
            const int b = id >= 41472, r2 = id - b * 41472, k = r2 / 72, c = r2 % 72;
            const int hh = k / 18, d = k % 18;
            const int kp = (hh >> 2) * 72 + (d < 16 ? (hh & 3) * 16 + d : 64 + (hh & 3) * 2 + (d - 16));
            if (threadIdx.x + q * 512 < 648) *(uint4*)(g_Wt + ((((c / 9) * 2 + b) * 4 + kp / 144) * 9 + (c % 9)) * 1152 + (kp % 144) * 8) = wv[q];
        }
    }

    const int h = cta >> 2, quarter = cta & 3;
    const uint32_t sPQ = sK + 2 * HEAD_BYTES, sKVt = sPQ + 24576;
    pdl_wait();
    TSTAMP(1, 1);
    auto issue_kv = [&](int c) {
        mbar_expect_tx(bar0 + 8 * c, 24576);
        bulk_g2s(sK + c * 12288, (const char*)(g_T + (size_t)(4 * NH + h) * HEAD_ELEMS) + c * 12288, 12288, bar0 + 8 * c);
        bulk_g2s(sV + c * 12288, (const char*)(g_T + (size_t)(5 * NH + h) * HEAD_ELEMS) + c * 12288, 12288, bar0 + 8 * c);
    };
    int kv_state = 0;
    auto kv_poll = [&](bool block) {
        if (threadIdx.x == 0 && kv_state != 2) {
            while (block && kv_state == 0) asm volatile("ld.acquire.gpu.global.b32 %0, [%1];" : "=r"(kv_state) : "l"(g_kvflag + h) : "memory");
            if (kv_state == 1) {
                asm volatile("fence.proxy.async.global;" ::: "memory");
                mbar_expect_tx(bar0 + 72, 1536);
                bulk_g2s(sKVt, g_kv + h * 768, 1536, bar0 + 72);
                kv_state = 2;
            } else {
                asm volatile("ld.acquire.gpu.global.b32 %0, [%1];" : "=r"(kv_state) : "l"(g_kvflag + h) : "memory");
            }
        }
    };
    float km2 = 0.f;
    #pragma unroll
    for (int i = 0; i < 8; i++) km2 = fmaxf(km2, g_kmax[i][h]);
    int s_fast_tmp = 0;
    uint32_t zr = 0u;
    asm volatile("" : "+r"(zr));
    uint32_t qf[2][6];
    #pragma unroll
    for (int pass = 0; pass < 2; pass++) {
        const int row0 = quarter * 512 + (wg * 2 + pass) * 64 + warp * 16 + g;
        const uint32_t* q0 = (const uint32_t*)(g_T + (size_t)(3 * NH + h) * HEAD_ELEMS + (row0 >> 3) * 192 + (row0 & 7) * 8) + t;
        qf[pass][0] = q0[0]; qf[pass][1] = q0[96]; qf[pass][2] = q0[32]; qf[pass][3] = q0[128];
        qf[pass][4] = q0[64]; qf[pass][5] = q0[160];
    }
    if (threadIdx.x == 0) issue_kv(0);
    if (threadIdx.x == 128) issue_kv(1);
    __syncwarp();
    float mrow[2][2];
    bool ok = true;
    #pragma unroll
    for (int pass = 0; pass < 2; pass++) {
        auto sq = [](uint32_t v) { float a = bf_lo(v), b = bf_hi(v); return a * a + b * b; };
        float n0 = sq(qf[pass][0]) + sq(qf[pass][2]) + sq(qf[pass][4]);
        float n1 = sq(qf[pass][1]) + sq(qf[pass][3]) + sq(qf[pass][5]);
        n0 += __shfl_xor_sync(~0u, n0, 1); n0 += __shfl_xor_sync(~0u, n0, 2);
        n1 += __shfl_xor_sync(~0u, n1, 1); n1 += __shfl_xor_sync(~0u, n1, 2);
        mrow[pass][0] = sqrtf(n0 * km2) * 1.01f + 0.01f;
        mrow[pass][1] = sqrtf(n1 * km2) * 1.01f + 0.01f;
        ok = ok && (mrow[pass][0] <= 31.0f) && (mrow[pass][1] <= 31.0f);
    }
    bool fast;
    asm volatile("{\n.reg .pred p, q;\nsetp.ne.b32 p, %1, 0;\nbar.red.and.pred q, %2, 128, p;\nselp.b32 %0, 1, 0, q;\n}\n"
                 : "=r"(*(int*)&s_fast_tmp) : "r"((int)ok), "r"(1 + wg) : "memory");
    fast = __all_sync(0xFFFFFFFFu, s_fast_tmp != 0);
    TSTAMP(1, 3);

    #pragma unroll 1
    for (int pass = 0; pass < 2; pass++) {
        const int row0 = quarter * 512 + (wg * 2 + pass) * 64 + warp * 16 + g;
        uint32_t qa[6];
        #pragma unroll
        for (int i = 0; i < 6; i++) qa[i] = pass ? qf[1][i] : qf[0][i];
        float o[12];
        #pragma unroll
        for (int i = 0; i < 12; i++) o[i] = 0.f;
        fence_regs(o);
        float s[64]; uint32_t p[32];
        #pragma unroll
        for (int i = 0; i < 64; i++) s[i] = 0.f;
        fence_regs(s);
        if (fast) {
            if (t == 1) { qa[4] = pack_bf16(-(pass ? mrow[1][0] : mrow[0][0]), 1.0f); qa[5] = pack_bf16(-(pass ? mrow[1][1] : mrow[0][1]), 1.0f); }
            #pragma unroll 1
            for (int j = 0; j < 16; j++) {
                if (pass == 0 && (j & 1) == 0) {
                    const int cn = (j >> 1) + 2;
                    if ((threadIdx.x & 127) == 0 && (cn & 3) == wg) {
                        if (cn < 8) issue_kv(cn);
                        else if (cn == 8) { mbar_expect_tx(bar0 + 64, 24576); bulk_g2s(sPQ, (const char*)(g_T + (size_t)h * HEAD_ELEMS) + quarter * 24576, 24576, bar0 + 64); }
                    }
                    mbar_wait_w(bar0 + 8 * (j >> 1), 0);
                }
                const uint32_t ko = j * 384;
                WG_FENCE();
                wgmma_n128_rs<0>(s, qa[0], qa[1], qa[2], qa[3], mkdesc(kd0 + ko, khi));
                wgmma_n128_rs<1>(s, qa[4], qa[5], zr, zr, mkdesc(kd1 + ko, khi));
                WG_COMMIT();
                if (pass == 1 && (j & 3) == 3) { kv_poll(false); __syncwarp(); }
                WG_WAIT(0);
                #pragma unroll
                for (int qd = 0; qd < 4; qd++) {
                    if (qd == 0) softmax_blocks<0, 4>(s, p);
                    if (qd == 1) softmax_blocks<4, 4>(s, p);
                    if (qd == 2) softmax_blocks<8, 4>(s, p);
                    if (qd == 3) softmax_blocks<12, 4>(s, p);
                    WG_FENCE();
                    wgmma_n24_rs(o, p[qd * 8 + 0], p[qd * 8 + 1], p[qd * 8 + 2], p[qd * 8 + 3], mkdesc(vd0 + ko + qd * 96, vhi));
                    wgmma_n24_rs(o, p[qd * 8 + 4], p[qd * 8 + 5], p[qd * 8 + 6], p[qd * 8 + 7], mkdesc(vd0 + ko + qd * 96 + 48, vhi));
                    WG_COMMIT();
                }
                WG_WAIT(0);
            }
        } else {
            float mr0 = -INFINITY, mr1 = -INFINITY;
            #pragma unroll 1
            for (int j = 0; j < 16; j++) {
                if (pass == 0 && (j & 1) == 0) {
                    const int cn = (j >> 1) + 2;
                    if ((threadIdx.x & 127) == 0 && (cn & 3) == wg) {
                        if (cn < 8) issue_kv(cn);
                        else if (cn == 8) { mbar_expect_tx(bar0 + 64, 24576); bulk_g2s(sPQ, (const char*)(g_T + (size_t)h * HEAD_ELEMS) + quarter * 24576, 24576, bar0 + 64); }
                    }
                    mbar_wait_w(bar0 + 8 * (j >> 1), 0);
                }
                const uint32_t ko = j * 384;
                WG_FENCE();
                wgmma_n128_rs<0>(s, qa[0], qa[1], qa[2], qa[3], mkdesc(kd0 + ko, khi));
                wgmma_n128_rs<1>(s, qa[4], qa[5], zr, zr, mkdesc(kd1 + ko, khi));
                WG_COMMIT();
                WG_WAIT(0);
                fence_regs(s); fence_regs(o);
                float x0 = mr0, x1 = mr1;
                #pragma unroll
                for (int b = 0; b < 16; b++) {
                    x0 = fmaxf(x0, fmaxf(s[4 * b], s[4 * b + 1]));
                    x1 = fmaxf(x1, fmaxf(s[4 * b + 2], s[4 * b + 3]));
                }
                x0 = fmaxf(x0, __shfl_xor_sync(~0u, x0, 1)); x0 = fmaxf(x0, __shfl_xor_sync(~0u, x0, 2));
                x1 = fmaxf(x1, __shfl_xor_sync(~0u, x1, 1)); x1 = fmaxf(x1, __shfl_xor_sync(~0u, x1, 2));
                const float c0 = exp2f(mr0 - x0), c1 = exp2f(mr1 - x1);
                mr0 = x0; mr1 = x1;
                #pragma unroll
                for (int i = 0; i < 12; i++) o[i] *= (i & 2) ? c1 : c0;
                #pragma unroll
                for (int b = 0; b < 16; b++) {
                    p[2 * b] = pack_bf16(exp2f(s[4 * b] - x0), exp2f(s[4 * b + 1] - x0));
                    p[2 * b + 1] = pack_bf16(exp2f(s[4 * b + 2] - x1), exp2f(s[4 * b + 3] - x1));
                }
                fence_regs(o);
                WG_FENCE();
                #pragma unroll
                for (int kk = 0; kk < 8; kk++)
                    wgmma_n24_rs(o, p[kk * 4 + 0], p[kk * 4 + 1], p[kk * 4 + 2], p[kk * 4 + 3], mkdesc(vd0 + ko + kk * 48, vhi));
                WG_COMMIT();
                WG_WAIT(0);
            }
        }
        fence_regs(o);
        const float l0 = __shfl_sync(~0u, o[8], (lane & ~3) | 1);
        const float l1 = __shfl_sync(~0u, o[10], (lane & ~3) | 1);
        store_o(1, row0, h, t, o, 1.0f / l0, 1.0f / l1);
    }
    TSTAMP(1, 4);
    {
        kv_poll(true); kv_poll(true);
        mbar_wait_w(bar0 + 64, 0);
        mbar_wait_w(bar0 + 72, 0);
        float e[4][12];
        #pragma unroll
        for (int k = 0; k < 4; k++) {
            #pragma unroll
            for (int i = 0; i < 12; i++) e[k][i] = 0.f;
            fence_regs(e[k]);
        }
        const uint32_t ab = (sPQ + wg * 6144) >> 4, bb = (sKVt >> 4) | (24u << 16);
        WG_FENCE();
        wgmma_n24_ss<0, 1>(e[0], mkdesc(ab | (8u << 16), khi), mkdesc(bb, vhi), 0);
        wgmma_n24_ss<0, 1>(e[1], mkdesc((ab + 192) | (8u << 16), khi), mkdesc(bb, vhi), 0);
        wgmma_n24_ss<0, 1>(e[2], mkdesc(ab + 16, khi), mkdesc(bb + 48, vhi), 0);
        wgmma_n24_ss<0, 1>(e[3], mkdesc(ab + 192 + 16, khi), mkdesc(bb + 48, vhi), 0);
        WG_COMMIT();
        WG_WAIT(0);
        #pragma unroll
        for (int k = 0; k < 4; k++) fence_regs(e[k]);
        #pragma unroll
        for (int m = 0; m < 2; m++) {
            #pragma unroll
            for (int i = 0; i < 12; i++) e[m][i] = bfr(e[m][i] + e[m + 2][i]);
            const float l0 = __shfl_sync(~0u, e[m][8], (lane & ~3) | 1), l1 = __shfl_sync(~0u, e[m][10], (lane & ~3) | 1);
            store_o(0, quarter * 512 + (wg * 2 + m) * 64 + warp * 16 + g, h, t, e[m], 1.0f / bfr(l0 + 1e-6f), 1.0f / bfr(l1 + 1e-6f));
        }
    }
    TSTAMP(1, 2);
}

#define K3_STAGES 4
#define K3_STAGE_BYTES 57600
#define K3_SMEM (K3_STAGES * K3_STAGE_BYTES + 1024)

__device__ __forceinline__ void cluster_sync() {
    asm volatile("barrier.cluster.arrive.release.aligned;\nbarrier.cluster.wait.acquire.aligned;" ::: "memory");
}

#define K3_CL 2
__global__ void __cluster_dims__(K3_CL, 1, 1) __launch_bounds__(288, 1)
out_kernel(__nv_bfloat16* __restrict__ out) {
    extern __shared__ unsigned char smem_raw[];
    __shared__ __align__(8) uint64_t bars[2 * K3_STAGES];
    const uint32_t sA = (smem_u32(smem_raw) + 1023u) & ~1023u;
    const uint32_t full0 = smem_u32(bars), empty0 = full0 + 8 * K3_STAGES;
    const int mt = blockIdx.x >> 3, nt = blockIdx.x & 7, rank = nt & (K3_CL - 1);
    const int m0 = mt * 128, n0 = nt * 72;
    TSTAMP(2, 0);
    if (threadIdx.x == 0) {
        for (int i = 0; i < K3_STAGES; i++) { mbar_init(full0 + 8 * i, 1); mbar_init(empty0 + 8 * i, 2 * K3_CL); }
        asm volatile("fence.mbarrier_init.release.cluster;" ::: "memory");
    }
    cluster_sync();
    TSTAMP(2, 3);
    pdl_wait();
    TSTAMP(2, 1);
    const int wg = threadIdx.x >> 7;
    if (wg == 2) {
        if (threadIdx.x == 256) {
            for (int c = 0; c < 8; c++) {
                const int s = c % K3_STAGES;
                if (c >= K3_STAGES) mbar_wait(empty0 + 8 * s, ((c / K3_STAGES) - 1) & 1);
                const uint32_t st = sA + s * K3_STAGE_BYTES;
                mbar_expect_tx(full0 + 8 * s, K3_STAGE_BYTES);
                const char* asrc = (const char*)(g_O + (size_t)(((c & 1) * 16 + mt) * 8 + 2 * (c >> 1)) * 9216) + rank * (36864 / K3_CL);
                asm volatile("cp.async.bulk.shared::cluster.global.mbarrier::complete_tx::bytes.multicast::cluster [%0], [%1], %2, [%3], %4;"
                             :: "r"(st + rank * (36864 / K3_CL)), "l"(asrc), "r"(36864 / K3_CL), "r"(full0 + 8 * s), "h"((uint16_t)((1 << K3_CL) - 1)) : "memory");
                bulk_g2s(st + 36864, g_Wt + (size_t)(nt * 8 + (c & 1) * 4 + (c >> 1)) * 10368, 20736, full0 + 8 * s);
            }
        }
        __syncwarp();
    } else {
        const int warp = (threadIdx.x >> 5) & 3, lane = threadIdx.x & 31, g = lane >> 2, t = lane & 3;
        float aa[36], ab[36];
        #pragma unroll
        for (int i = 0; i < 36; i++) { aa[i] = 0.f; ab[i] = 0.f; }
        fence_regs(aa); fence_regs(ab);
        const uint32_t hiA = 72u;
        const uint32_t hiB = 144u;
        const int r0 = m0 + wg * 64 + warp * 16 + g;
        const float g0 = g_gate[r0], g1 = g_gate[r0 + 8];
        #pragma unroll 1
        for (int pr = 0; pr < 4; pr++) {
            const int s = (pr & 1) * 2;
            mbar_wait_w(full0 + 8 * s, pr >> 1);
            mbar_wait_w(full0 + 8 * s + 8, pr >> 1);
            const uint32_t a_lo = ((sA + s * K3_STAGE_BYTES + wg * 9216) & 0x3FFFF) >> 4;
            const uint32_t b_lo = (((sA + s * K3_STAGE_BYTES + 36864) & 0x3FFFF) >> 4) | (8u << 16);
            WG_FENCE();
            #pragma unroll
            for (int i = 0; i < 9; i++) {
                const uint32_t ad = i < 4 ? (a_lo + i * 16) | (8u << 16) : i == 4 ? (a_lo + 64) | (1088u << 16) : (a_lo + 1152 + 8 + (i - 5) * 16) | (8u << 16);
                wgmma_n72_ss(aa, mkdesc(ad, hiA), mkdesc(b_lo + i * 16, hiB), 1);
                wgmma_n72_ss(ab, mkdesc(ad + K3_STAGE_BYTES / 16, hiA), mkdesc(b_lo + i * 16 + K3_STAGE_BYTES / 16, hiB), 1);
            }
            WG_COMMIT();
            if (pr < 2) {
                WG_WAIT(0);
                if ((threadIdx.x & 127) < 2 * K3_CL) {
                    uint32_t ra;
                    asm volatile("mapa.shared::cluster.u32 %0, %1, %2;" : "=r"(ra) : "r"(empty0 + 8 * (s + ((threadIdx.x / K3_CL) & 1))), "r"(threadIdx.x & (K3_CL - 1)));
                    asm volatile("mbarrier.arrive.release.cluster.shared::cluster.b64 _, [%0];" :: "r"(ra) : "memory");
                }
            }
        }
        WG_WAIT(0);
        fence_regs(aa); fence_regs(ab);
        const float h0 = bfr(1.0f - g0), h1 = bfr(1.0f - g1);
        uint32_t* o0 = (uint32_t*)(out + (size_t)r0 * DM + n0) + t;
        uint32_t* o1 = (uint32_t*)(out + (size_t)(r0 + 8) * DM + n0) + t;
        #pragma unroll
        for (int j = 0; j < 9; j++) {
            float v0 = bfr(g0 * bfr(aa[4 * j])) + bfr(h0 * bfr(ab[4 * j]));
            float v1 = bfr(g0 * bfr(aa[4 * j + 1])) + bfr(h0 * bfr(ab[4 * j + 1]));
            float v2 = bfr(g1 * bfr(aa[4 * j + 2])) + bfr(h1 * bfr(ab[4 * j + 2]));
            float v3 = bfr(g1 * bfr(aa[4 * j + 3])) + bfr(h1 * bfr(ab[4 * j + 3]));
            o0[4 * j] = pack_bf16(v0, v1);
            o1[4 * j] = pack_bf16(v2, v3);
        }
        TSTAMP(2, 2);
    }
    cluster_sync();
}

typedef CUresult (*EncodeFn)(CUtensorMap*, CUtensorMapDataType, cuuint32_t, void*, const cuuint64_t*, const cuuint64_t*,
                             const cuuint32_t*, const cuuint32_t*, CUtensorMapInterleave, CUtensorMapSwizzle,
                             CUtensorMapL2promotion, CUtensorMapFloatOOBfill);

static void make_map(EncodeFn enc, CUtensorMap* m, const void* base, uint64_t inner, uint64_t outer, uint32_t box_in, uint32_t box_out, CUtensorMapSwizzle sw) {
    cuuint64_t dims[2] = {inner, outer};
    cuuint64_t strides[1] = {inner * 2};
    cuuint32_t box[2] = {box_in, box_out};
    cuuint32_t es[2] = {1, 1};
    enc(m, CU_TENSOR_MAP_DATA_TYPE_BFLOAT16, 2, (void*)base, dims, strides, box, es, CU_TENSOR_MAP_INTERLEAVE_NONE, sw,
        CU_TENSOR_MAP_L2_PROMOTION_L2_256B, CU_TENSOR_MAP_FLOAT_OOB_FILL_NONE);
}

extern "C" void kernel_launch(void* const* d_in, const int* in_sizes, int n_in, void* d_out, int out_size) {
    const __nv_bfloat16* x = (const __nv_bfloat16*)d_in[0];
    const __nv_bfloat16* wA = (const __nv_bfloat16*)d_in[1];
    const __nv_bfloat16* woA = (const __nv_bfloat16*)d_in[2];
    const __nv_bfloat16* wB = (const __nv_bfloat16*)d_in[4];
    const __nv_bfloat16* woB = (const __nv_bfloat16*)d_in[5];
    const __nv_bfloat16* gw = (const __nv_bfloat16*)d_in[6];
    __nv_bfloat16* out = (__nv_bfloat16*)d_out;

    static EncodeFn enc = nullptr;
    if (!enc) {
        void* fn = nullptr; cudaDriverEntryPointQueryResult st;
        cudaGetDriverEntryPoint("cuTensorMapEncodeTiled", &fn, cudaEnableDefault, &st);
        enc = (EncodeFn)fn;
        cudaFuncSetAttribute(qkv_kernel, cudaFuncAttributeMaxDynamicSharedMemorySize, K1_SMEM);
        cudaFuncSetAttribute(attn_kernel, cudaFuncAttributeMaxDynamicSharedMemorySize, K2_SMEM);
        cudaFuncSetAttribute(out_kernel, cudaFuncAttributeMaxDynamicSharedMemorySize, K3_SMEM);
    }
    CUtensorMap mX, mWA, mWA2, mWB, mWB2;
    make_map(enc, &mX, x, DM, S_LEN, 64, 256, CU_TENSOR_MAP_SWIZZLE_128B);
    make_map(enc, &mWA, wA, 3 * DM, DM, 64, 64, CU_TENSOR_MAP_SWIZZLE_128B);
    make_map(enc, &mWA2, wA, 3 * DM, DM, 32, 64, CU_TENSOR_MAP_SWIZZLE_64B);
    make_map(enc, &mWB, wB, 3 * DM, DM, 64, 64, CU_TENSOR_MAP_SWIZZLE_128B);
    make_map(enc, &mWB2, wB, 3 * DM, DM, 32, 64, CU_TENSOR_MAP_SWIZZLE_64B);

    cudaStream_t stream = cudaStreamPerThread;
    cudaLaunchAttribute at[1];
    at[0].id = cudaLaunchAttributeProgrammaticStreamSerialization;
    at[0].val.programmaticStreamSerializationAllowed = 1;

    qkv_kernel<<<128, 256, K1_SMEM, stream>>>(mX, mWA, mWA2, mWB, mWB2);

    cudaLaunchConfig_t c2 = {};
    c2.gridDim = dim3(132); c2.blockDim = dim3(512); c2.dynamicSmemBytes = K2_SMEM; c2.stream = stream; c2.attrs = at; c2.numAttrs = 1;
    cudaLaunchKernelEx(&c2, attn_kernel, x, gw, woA, woB);

    cudaLaunchConfig_t c3 = {};
    c3.gridDim = dim3(128); c3.blockDim = dim3(288); c3.dynamicSmemBytes = K3_SMEM; c3.stream = stream; c3.attrs = at; c3.numAttrs = 1;
    cudaLaunchKernelEx(&c3, out_kernel, out);
}
```

```cpp
#include <cuda_runtime.h>
#include <cuda_bf16.h>
#include <cuda.h>
#include <stdint.h>

#define S_LEN 2048
#define DM 576
#define NH 32
#define DH 18
#define HEAD_ELEMS 49152
#define HEAD_BYTES 98304

#define POLY_BLK 0xAAAA

__device__ __align__(1024) __nv_bfloat16 g_T[6 * NH * HEAD_ELEMS];
__device__ float g_kmax[8][NH];
__device__ __align__(1024) __nv_bfloat16 g_O[2 * S_LEN * DM];
__device__ float g_gate[S_LEN];
__device__ __align__(128) __nv_bfloat16 g_kv[NH * 768];
__device__ int g_kvflag[NH];
__device__ __align__(1024) __nv_bfloat16 g_Wt[6 * 2 * 4 * 13824];

#define TSTAMP(k, i)
#define WG_FENCE() asm volatile("wgmma.fence.sync.aligned;\n" ::: "memory")
#define WG_COMMIT() asm volatile("wgmma.commit_group.sync.aligned;\n" ::: "memory")
#define WG_WAIT(n) asm volatile("wgmma.wait_group.sync.aligned %0;\n" :: "n"(n) : "memory")

__device__ __forceinline__ uint64_t mkdesc(uint32_t lo, uint32_t hi) {
    uint64_t d; asm("mov.b64 %0, {%1, %2};" : "=l"(d) : "r"(lo), "r"(hi)); return d;
}
__device__ __forceinline__ uint32_t smem_u32(const void* p) { return (uint32_t)__cvta_generic_to_shared(p); }
__device__ __forceinline__ void mbar_init(uint32_t bar, uint32_t cnt) { asm volatile("mbarrier.init.shared::cta.b64 [%0], %1;" :: "r"(bar), "r"(cnt)); }
__device__ __forceinline__ void mbar_expect_tx(uint32_t bar, uint32_t bytes) { asm volatile("mbarrier.arrive.expect_tx.shared::cta.b64 _, [%0], %1;" :: "r"(bar), "r"(bytes) : "memory"); }
__device__ __forceinline__ void mbar_arrive(uint32_t bar) { asm volatile("mbarrier.arrive.shared::cta.b64 _, [%0];" :: "r"(bar) : "memory"); }
__device__ __forceinline__ void mbar_wait(uint32_t bar, uint32_t parity) {
    asm volatile("{\n.reg .pred p;\nWAIT_%=:\nmbarrier.try_wait.parity.shared::cta.b64 p, [%0], %1;\n@p bra DONE_%=;\nbra WAIT_%=;\nDONE_%=:\n}\n" :: "r"(bar), "r"(parity) : "memory");
}
__device__ __forceinline__ void mbar_wait_w(uint32_t bar, uint32_t parity) { __syncwarp(); mbar_wait(bar, parity); }
__device__ __forceinline__ void bulk_g2s(uint32_t dst, const void* src, uint32_t bytes, uint32_t bar) {
    asm volatile("cp.async.bulk.shared::cluster.global.mbarrier::complete_tx::bytes [%0], [%1], %2, [%3];" :: "r"(dst), "l"(src), "r"(bytes), "r"(bar) : "memory");
}
__device__ __forceinline__ void tma_2d(uint32_t dst, const CUtensorMap* map, int c0, int c1, uint32_t bar) {
    asm volatile("cp.async.bulk.tensor.2d.shared::cluster.global.mbarrier::complete_tx::bytes [%0], [%1, {%3, %4}], [%2];"
                 :: "r"(dst), "l"((uint64_t)map), "r"(bar), "r"(c0), "r"(c1) : "memory");
}
__device__ __forceinline__ void tma_3d(uint32_t dst, const CUtensorMap* map, int c0, int c1, int c2, uint32_t bar) {
    asm volatile("cp.async.bulk.tensor.3d.shared::cluster.global.mbarrier::complete_tx::bytes [%0], [%1, {%3, %4, %5}], [%2];"
                 :: "r"(dst), "l"((uint64_t)map), "r"(bar), "r"(c0), "r"(c1), "r"(c2) : "memory");
}
__device__ __forceinline__ void cluster_arrive() { asm volatile("barrier.cluster.arrive.release.aligned;" ::: "memory"); }
__device__ __forceinline__ void cluster_wait() { asm volatile("barrier.cluster.wait.acquire.aligned;" ::: "memory"); }
__device__ __forceinline__ void cluster_sync() { cluster_arrive(); cluster_wait(); }
__device__ __forceinline__ void mbar_arrive_cta(uint32_t bar, uint32_t cta) {
    uint32_t ra;
    asm volatile("mapa.shared::cluster.u32 %0, %1, %2;" : "=r"(ra) : "r"(bar), "r"(cta));
    asm volatile("mbarrier.arrive.release.cluster.shared::cluster.b64 _, [%0];" :: "r"(ra) : "memory");
}
__device__ __forceinline__ void named_bar(int id, int n) { asm volatile("bar.sync %0, %1;" :: "r"(id), "r"(n) : "memory"); }
__device__ __forceinline__ void fence_async() { asm volatile("fence.proxy.async.shared::cta;" ::: "memory"); }
__device__ __forceinline__ void pdl_wait() { asm volatile("griddepcontrol.wait;" ::: "memory"); }
__device__ __forceinline__ void pdl_launch() { asm volatile("griddepcontrol.launch_dependents;" ::: "memory"); }

__device__ __forceinline__ float ex2f(float x) { float y; asm("ex2.approx.ftz.f32 %0, %1;" : "=f"(y) : "f"(x)); return y; }
__device__ __forceinline__ uint32_t pack_bf16(float lo, float hi) { uint32_t r; asm("cvt.rn.bf16x2.f32 %0, %1, %2;" : "=r"(r) : "f"(hi), "f"(lo)); return r; }
__device__ __forceinline__ float bf_lo(uint32_t v) { return __uint_as_float(v << 16); }
__device__ __forceinline__ float bf_hi(uint32_t v) { return __uint_as_float(v & 0xFFFF0000u); }
__device__ __forceinline__ float bfr(float x) { return __uint_as_float(pack_bf16(0.f, x) & 0xFFFF0000u); }

#define ACC4(a, o) "+f"(a[o]), "+f"(a[o + 1]), "+f"(a[o + 2]), "+f"(a[o + 3])
#define ACC12(a, o) ACC4(a, o), ACC4(a, o + 4), ACC4(a, o + 8)
#define ACC16(a, o) ACC4(a, o), ACC4(a, o + 4), ACC4(a, o + 8), ACC4(a, o + 12)
#define ACC32(a, o) ACC16(a, o), ACC16(a, o + 16)

__device__ __forceinline__ void wgmma_n24_rs(float (&d)[12], uint32_t a0, uint32_t a1, uint32_t a2, uint32_t a3, uint64_t bdesc) {
    asm volatile("{\n.reg .pred p;\nsetp.ne.b32 p, 1, 0;\n"
        "wgmma.mma_async.sync.aligned.m64n24k16.f32.bf16.bf16 "
        "{%0,%1,%2,%3,%4,%5,%6,%7,%8,%9,%10,%11}, {%12,%13,%14,%15}, %16, p, 1, 1, 1;\n}\n"
        : ACC12(d, 0) : "r"(a0), "r"(a1), "r"(a2), "r"(a3), "l"(bdesc));
}
template<int TA, int TB>
__device__ __forceinline__ void wgmma_n24_ss(float (&d)[12], uint64_t adesc, uint64_t bdesc, int acc) {
    asm volatile("{\n.reg .pred p;\nsetp.ne.b32 p, %14, 0;\n"
        "wgmma.mma_async.sync.aligned.m64n24k16.f32.bf16.bf16 "
        "{%0,%1,%2,%3,%4,%5,%6,%7,%8,%9,%10,%11}, %12, %13, p, 1, 1, %15, %16;\n}\n"
        : ACC12(d, 0) : "l"(adesc), "l"(bdesc), "r"(acc), "n"(TA), "n"(TB));
}
template<int ACC>
__device__ __forceinline__ void wgmma_n128_rs(float (&d)[64], uint32_t a0, uint32_t a1, uint32_t a2, uint32_t a3, uint64_t bdesc) {
    asm volatile("{\n.reg .pred p;\nsetp.ne.b32 p, %69, 0;\n"
        "wgmma.mma_async.sync.aligned.m64n128k16.f32.bf16.bf16 "
        "{%0,%1,%2,%3,%4,%5,%6,%7,%8,%9,%10,%11,%12,%13,%14,%15,%16,%17,%18,%19,%20,%21,%22,%23,%24,%25,%26,%27,%28,%29,%30,%31,"
        "%32,%33,%34,%35,%36,%37,%38,%39,%40,%41,%42,%43,%44,%45,%46,%47,%48,%49,%50,%51,%52,%53,%54,%55,%56,%57,%58,%59,%60,%61,%62,%63}, {%64,%65,%66,%67}, %68, p, 1, 1, 0;\n}\n"
        : ACC32(d, 0), ACC32(d, 32) : "r"(a0), "r"(a1), "r"(a2), "r"(a3), "l"(bdesc), "n"(ACC));
}
__device__ __forceinline__ void wgmma_n192_ss(float (&d)[96], uint64_t adesc, uint64_t bdesc, int acc) {
    asm volatile("{\n.reg .pred p;\nsetp.ne.b32 p, %98, 0;\n"
        "wgmma.mma_async.sync.aligned.m64n192k16.f32.bf16.bf16 "
        "{%0,%1,%2,%3,%4,%5,%6,%7,%8,%9,%10,%11,%12,%13,%14,%15,%16,%17,%18,%19,%20,%21,%22,%23,%24,%25,%26,%27,%28,%29,%30,%31,"
        "%32,%33,%34,%35,%36,%37,%38,%39,%40,%41,%42,%43,%44,%45,%46,%47,%48,%49,%50,%51,%52,%53,%54,%55,%56,%57,%58,%59,%60,%61,%62,%63,"
        "%64,%65,%66,%67,%68,%69,%70,%71,%72,%73,%74,%75,%76,%77,%78,%79,%80,%81,%82,%83,%84,%85,%86,%87,%88,%89,%90,%91,%92,%93,%94,%95}, %96, %97, p, 1, 1, 0, 1;\n}\n"
        : ACC32(d, 0), ACC32(d, 32), ACC32(d, 64) : "l"(adesc), "l"(bdesc), "r"(acc));
}
__device__ __forceinline__ void wgmma_n96_ss(float (&d)[48], uint64_t adesc, uint64_t bdesc) {
    asm volatile("{\n.reg .pred p;\nsetp.ne.b32 p, 1, 0;\n"
        "wgmma.mma_async.sync.aligned.m64n96k16.f32.bf16.bf16 "
        "{%0,%1,%2,%3,%4,%5,%6,%7,%8,%9,%10,%11,%12,%13,%14,%15,%16,%17,%18,%19,%20,%21,%22,%23,%24,%25,%26,%27,%28,%29,%30,%31,%32,%33,%34,%35,%36,%37,%38,%39,%40,%41,%42,%43,%44,%45,%46,%47}, %48, %49, p, 1, 1, 0, 1;\n}\n"
        : ACC32(d, 0), ACC16(d, 32) : "l"(adesc), "l"(bdesc));
}
template<int N> __device__ __forceinline__ void fence_regs(float (&d)[N]) {
    #pragma unroll
    for (int i = 0; i < N; i++) asm volatile("" : "+f"(d[i]) :: "memory");
}

#define K1_STAGES 3
#define K1_STAGE_BYTES 61440
#define K1_SMEM (K1_STAGES * K1_STAGE_BYTES + 1024)
#define STG_PITCH 436

__device__ __forceinline__ uint32_t hadd2_bf16(uint32_t a, uint32_t b) { uint32_t r; asm("add.rn.bf16x2 %0, %1, %2;" : "=r"(r) : "r"(a), "r"(b)); return r; }
__device__ __forceinline__ uint32_t phi_pair(uint32_t w) {
    const uint32_t p1 = hadd2_bf16(w, 0x3F803F80u);
    const uint32_t pe = pack_bf16(ex2f(bf_lo(w) * 1.4426950408889634f), ex2f(bf_hi(w) * 1.4426950408889634f));
    uint32_t m; asm("prmt.b32 %0, %1, 0, 0xBB99;" : "=r"(m) : "r"(w));
    const uint32_t r = (pe & m) | (p1 & ~m);
    return pack_bf16(bf_lo(r) + 1e-6f, bf_hi(r) + 1e-6f);
}
template<int N> __device__ __forceinline__ void phi_inplace(unsigned char* p, int tid) {
    uint4 v[N];
    #pragma unroll
    for (int i = 0; i < N; i++) v[i] = *(uint4*)(p + (i * 128 + tid) * 16);
    #pragma unroll
    for (int i = 0; i < N; i++) {
        v[i].x = phi_pair(v[i].x); v[i].y = phi_pair(v[i].y); v[i].z = phi_pair(v[i].z); v[i].w = phi_pair(v[i].w);
        *(uint4*)(p + (i * 128 + tid) * 16) = v[i];
    }
    fence_async();
}
__device__ __forceinline__ void phi36(uint32_t (&w)[36]) {
    #pragma unroll
    for (int i = 0; i < 36; i++) w[i] = phi_pair(w[i]);
}
__device__ __forceinline__ uint32_t qscale_pair(uint32_t w) {
    const float qs = 0.23570226039551584f * 1.4426950408889634f;
    return pack_bf16(bf_lo(w) * qs, bf_hi(w) * qs);
}
__device__ __forceinline__ void sts32(uint32_t addr, uint32_t v) { asm volatile("st.shared.b32 [%0], %1;" :: "r"(addr), "r"(v) : "memory"); }

__global__ void __launch_bounds__(256, 1)
qkv_kernel(const __grid_constant__ CUtensorMap mapX, const __grid_constant__ CUtensorMap mapWA, const __grid_constant__ CUtensorMap mapWA2,
           const __grid_constant__ CUtensorMap mapWB, const __grid_constant__ CUtensorMap mapWB2) {
    extern __shared__ unsigned char smem_raw[];
    __shared__ __align__(8) uint64_t bars[2 * K1_STAGES];
    __shared__ uint32_t s_nmax[12];
    const uint32_t sbase = (smem_u32(smem_raw) + 1023u) & ~1023u;
    unsigned char* stg = smem_raw + (sbase - smem_u32(smem_raw));
    const uint32_t full0 = smem_u32(bars), empty0 = full0 + 8 * K1_STAGES;
    const int mt = blockIdx.x >> 4, nt = blockIdx.x & 15;
    const int branch = nt >> 3, n0 = (nt & 7) * 216, m0 = mt * 256;
    const int wg = threadIdx.x >> 7;
    const int warp = (threadIdx.x >> 5) & 3, lane = threadIdx.x & 31, g = lane >> 2, t = lane & 3;
    TSTAMP(0, 0);
    const CUtensorMap* w1 = branch ? &mapWB : &mapWA;
    const CUtensorMap* w2 = branch ? &mapWB2 : &mapWA2;
    auto issue = [&](int kt, int part) {
        const int s = kt % K1_STAGES;
        const uint32_t st = sbase + s * K1_STAGE_BYTES, fb = full0 + 8 * s;
        if (part == 0) {
            mbar_expect_tx(fb, K1_STAGE_BYTES);
            tma_2d(st, &mapX, kt * 64, m0, fb);
            tma_2d(st + 32768 + 24576, w2, n0 + 192, kt * 64, fb);
        } else {
            tma_2d(st + 32768, w1, n0, kt * 64, fb);
            tma_2d(st + 32768 + 8192, w1, n0 + 64, kt * 64, fb);
            tma_2d(st + 32768 + 16384, w1, n0 + 128, kt * 64, fb);
        }
    };
    if (threadIdx.x == 0) {
        for (int i = 0; i < K1_STAGES; i++) { mbar_init(full0 + 8 * i, 1); mbar_init(empty0 + 8 * i, 2); }
        asm volatile("fence.mbarrier_init.release.cluster;" ::: "memory");
        issue(0, 0); issue(0, 1);
    }
    if (threadIdx.x >= 64 && threadIdx.x < 76) s_nmax[threadIdx.x - 64] = 0;
    if (blockIdx.x == 0 && threadIdx.x >= 32 && threadIdx.x < 64) g_kvflag[threadIdx.x - 32] = 0;
    __syncthreads();
    if (lane == 0 && threadIdx.x < 128) issue(1 + (threadIdx.x >> 6), (threadIdx.x >> 5) & 1);
    pdl_launch();
    const uint32_t hiA = 64u | 0x40000000u;
    const uint32_t hiB = 64u | 0x40000000u;
    const uint32_t hiB2 = 32u | 0x80000000u;
    float acc0[96], acc1[96], acd0[12], acd1[12];
    #pragma unroll
    for (int i = 0; i < 96; i++) { acc0[i] = 0.f; acc1[i] = 0.f; }
    #pragma unroll
    for (int i = 0; i < 12; i++) { acd0[i] = 0.f; acd1[i] = 0.f; }
    fence_regs(acc0); fence_regs(acc1); fence_regs(acd0); fence_regs(acd1);
    #pragma unroll 1
    for (int kt = 0; kt < 9; kt++) {
        const int s = kt % K1_STAGES;
        mbar_wait_w(full0 + 8 * s, (kt / K1_STAGES) & 1);
        const uint32_t st = sbase + s * K1_STAGE_BYTES;
        const uint32_t a_lo = ((st + wg * 16384) >> 4) | (1u << 16);
        const uint32_t b_lo = ((st + 32768) >> 4) | (512u << 16);
        const uint32_t b2_lo = ((st + 32768 + 24576) >> 4) | (1u << 16);
        WG_FENCE();
        #pragma unroll
        for (int kk = 0; kk < 4; kk++) {
            wgmma_n192_ss(acc0, mkdesc(a_lo + kk * 2, hiA), mkdesc(b_lo + kk * 128, hiB), 1);
            wgmma_n24_ss<0, 1>(acd0, mkdesc(a_lo + kk * 2, hiA), mkdesc(b2_lo + kk * 64, hiB2), 1);
            wgmma_n192_ss(acc1, mkdesc(a_lo + 512 + kk * 2, hiA), mkdesc(b_lo + kk * 128, hiB), 1);
            wgmma_n24_ss<0, 1>(acd1, mkdesc(a_lo + 512 + kk * 2, hiA), mkdesc(b2_lo + kk * 64, hiB2), 1);
        }
        WG_COMMIT();
        WG_WAIT(1);
        if (kt > 0 && kt + 2 < 9) {
            const int sp = (kt - 1) % K1_STAGES;
            if ((threadIdx.x & 127) == 0) mbar_arrive(empty0 + 8 * sp);
            if (warp == 0) {
                mbar_wait_w(empty0 + 8 * sp, ((kt - 1) / K1_STAGES) & 1);
                if (lane == 0) issue(kt + 2, wg);
            }
            __syncwarp();
        }
    }
    WG_WAIT(0);
    fence_regs(acc0); fence_regs(acc1); fence_regs(acd0); fence_regs(acd1);
    TSTAMP(0, 1);
    __syncthreads();
    {
        uint32_t off9[9];
        #pragma unroll
        for (int jj = 0; jj < 9; jj++) {
            const int c = 8 * jj + 2 * t, hh = c / 18, d = c - hh * 18;
            off9[jj] = hh * 12288 + (d >> 3) * 128 + (d & 7) * 2;
        }
        const uint32_t base = sbase + (wg * 16 + warp * 2) * 384 + g * 16;
        const int k0 = branch * 3 + n0 / 576, k1 = branch * 3 + (n0 + 72) / 576, k2 = branch * 3 + (n0 + 144) / 576;
        const int row = threadIdx.x;
        const uint32_t pmagic = ((POLY_BLK >> ((row & 127) >> 3)) & 1) ? 0x46013F80u : 0x3F803F80u;
        const uint32_t pa = sbase + (row >> 3) * 384 + 256 + (row & 7) * 16 + 4;
        #pragma unroll
        for (int hh = 0; hh < 12; hh++) {
            const int kind = hh < 4 ? k0 : hh < 8 ? k1 : k2;
            sts32(pa + hh * 12288, kind == 4 ? pmagic : (kind == 2 || kind == 5) ? 0x00003F80u : 0u);
            asm volatile("st.shared.v2.b32 [%0], {%1, %1};" :: "r"(pa + hh * 12288 + 4), "r"(0u) : "memory");
        }
        auto flush = [&](int grp) {
            fence_async();
            __syncthreads();
            if (lane == 0 && threadIdx.x < 128) {
                const int hh = grp * 4 + (threadIdx.x >> 5), col0 = n0 + hh * 18;
                const int type = col0 / 576, head = (col0 % 576) / 18, kind = branch * 3 + type;
                const size_t hb = (kind == 1 || kind == 2) ? (size_t)(NH + 2 * head) * HEAD_ELEMS + mt * 12288 + (kind - 1) * 6144
                                                           : (size_t)(kind * NH + head) * HEAD_ELEMS + mt * 6144;
                asm volatile("cp.async.bulk.global.shared::cta.bulk_group [%0], [%1], %2;" :: "l"(g_T + hb), "r"(sbase + hh * 12288), "r"(12288) : "memory");
                asm volatile("cp.async.bulk.commit_group;" ::: "memory");
            }
            __syncwarp();
        };
        #pragma unroll
        for (int grp = 0; grp < 3; grp++) {
            uint32_t w[36];
            #pragma unroll
            for (int jj = 0; jj < 9; jj++) {
                const int j = grp * 9 + jj;
                if (j < 24) {
                    w[4 * jj] = pack_bf16(acc0[(4 * j) % 96], acc0[(4 * j + 1) % 96]); w[4 * jj + 1] = pack_bf16(acc0[(4 * j + 2) % 96], acc0[(4 * j + 3) % 96]);
                    w[4 * jj + 2] = pack_bf16(acc1[(4 * j) % 96], acc1[(4 * j + 1) % 96]); w[4 * jj + 3] = pack_bf16(acc1[(4 * j + 2) % 96], acc1[(4 * j + 3) % 96]);
                } else {
                    w[4 * jj] = pack_bf16(acd0[(4 * j) % 12], acd0[(4 * j + 1) % 12]); w[4 * jj + 1] = pack_bf16(acd0[(4 * j + 2) % 12], acd0[(4 * j + 3) % 12]);
                    w[4 * jj + 2] = pack_bf16(acd1[(4 * j) % 12], acd1[(4 * j + 1) % 12]); w[4 * jj + 3] = pack_bf16(acd1[(4 * j + 2) % 12], acd1[(4 * j + 3) % 12]);
                }
            }
            if ((grp == 0 ? k0 : grp == 1 ? k1 : k2) == 1) phi36(w);
            #pragma unroll
            for (int jj = 0; jj < 9; jj++) {
                const uint32_t a = base + grp * 49152 + off9[jj];
                sts32(a, w[4 * jj]); sts32(a + 384, w[4 * jj + 1]); sts32(a + 3072, w[4 * jj + 2]); sts32(a + 3456, w[4 * jj + 3]);
            }
            flush(grp);
        }
        TSTAMP(0, 3);
        #pragma unroll 1
        for (int grp = 0; grp < 3; grp++) {
            if ((grp == 0 ? k0 : grp == 1 ? k1 : k2) == 4) {
                #pragma unroll 2
                for (int hq = 0; hq < 4; hq++) {
                    const unsigned char* src = stg + (grp * 4 + hq) * 12288 + (row >> 3) * 384 + (row & 7) * 16;
                    const uint4 v0 = *(const uint4*)src, v1 = *(const uint4*)(src + 128);
                    const uint32_t w[9] = {v0.x, v0.y, v0.z, v0.w, v1.x, v1.y, v1.z, v1.w, *(const uint32_t*)(src + 256)};
                    float n2 = 0.f;
                    #pragma unroll
                    for (int i = 0; i < 9; i++) { const float a = bf_lo(w[i]), b = bf_hi(w[i]); n2 = fmaf(a, a, n2); n2 = fmaf(b, b, n2); }
                    uint32_t nb = __float_as_uint(n2);
                    if (!(n2 >= 0.f)) nb = 0x7F800000u;
                    nb = __reduce_max_sync(0xFFFFFFFFu, nb);
                    if (lane == 0) atomicMax(&s_nmax[grp * 4 + hq], nb);
                }
            }
        }
        __syncthreads();
        if (threadIdx.x < 12) {
            const int col0 = n0 + threadIdx.x * 18;
            if (branch == 1 && col0 / 576 == 1) g_kmax[mt][(col0 % 576) / 18] = __uint_as_float(s_nmax[threadIdx.x]);
        }
        if (lane == 0 && threadIdx.x < 128) asm volatile("cp.async.bulk.wait_group.read 0;" ::: "memory");
    }
    TSTAMP(0, 2);
}

__device__ __forceinline__ uint32_t hfma2(uint32_t a, uint32_t b, uint32_t c) { uint32_t r; asm("fma.rn.f16x2 %0, %1, %2, %3;" : "=r"(r) : "r"(a), "r"(b), "r"(c)); return r; }
__device__ __forceinline__ uint32_t and_or(uint32_t a, uint32_t m, uint32_t o) { uint32_t r; asm("lop3.b32 %0, %1, %2, %3, 0xEA;" : "=r"(r) : "r"(a), "r"(m), "r"(o)); return r; }
__device__ __forceinline__ uint32_t poly_ex2_pair(float t0, float t1) {
    const uint32_t u = __byte_perm(__float_as_uint(t0), __float_as_uint(t1), 0x5410);
    const uint32_t m = and_or(u, 0x03FF03FFu, 0x3C003C00u);
    uint32_t y = hfma2(m, 0x2CFE2CFEu, 0xA019A019u);
    y = hfma2(y, m, 0xB82EB82Eu);
    y = hfma2(y, m, 0x3FCF3FCFu);
    const uint32_t w = u + y + 0xC203C204u;
    return and_or(w >> 3, 0x1FFF1FFFu, 0x20002000u);
}

template<int B0, int NB>
__device__ __forceinline__ void softmax_blocks(float (&s)[64], uint32_t (&p)[32]) {
    #pragma unroll
    for (int i = B0 * 4; i < (B0 + NB) * 4; i++) asm volatile("" : "+f"(s[i]) :: "memory");
    #pragma unroll
    for (int b = B0; b < B0 + NB; b++) {
        if ((POLY_BLK >> b) & 1) {
            p[2 * b + 0] = poly_ex2_pair(s[4 * b], s[4 * b + 1]);
            p[2 * b + 1] = poly_ex2_pair(s[4 * b + 2], s[4 * b + 3]);
        } else {
            p[2 * b + 0] = pack_bf16(ex2f(s[4 * b]), ex2f(s[4 * b + 1]));
            p[2 * b + 1] = pack_bf16(ex2f(s[4 * b + 2]), ex2f(s[4 * b + 3]));
        }
    }
}

__device__ __forceinline__ void store_o(int branch, int row0, int h, int t, const float (&o)[12], float r0, float r1) {
    uint32_t* p = (uint32_t*)g_O + ((((branch * 16 + (row0 >> 7)) * 8 + (h >> 2)) * 16 + ((row0 >> 3) & 15)) * 72 + (row0 & 7)) * 4;
    uint32_t* q = p + (h & 3) * 64 + t;
    q[0] = pack_bf16(o[0] * r0, o[1] * r0); q[288] = pack_bf16(o[2] * r1, o[3] * r1);
    q[32] = pack_bf16(o[4] * r0, o[5] * r0); q[288 + 32] = pack_bf16(o[6] * r1, o[7] * r1);
    if (t == 0) { p[256 + (h & 3)] = pack_bf16(o[8] * r0, o[9] * r0); p[288 + 256 + (h & 3)] = pack_bf16(o[10] * r1, o[11] * r1); }
}

#define K2_SMEM (2 * HEAD_BYTES + 24576 + 1536 + 1024)

__global__ void __launch_bounds__(512, 1)
attn_kernel(const __nv_bfloat16* __restrict__ x, const __nv_bfloat16* __restrict__ gate_w,
            const __nv_bfloat16* __restrict__ woA, const __nv_bfloat16* __restrict__ woB) {
    extern __shared__ unsigned char smem_raw[];
    __shared__ __align__(8) uint64_t bars[16];
    const uint32_t sK = (smem_u32(smem_raw) + 1023u) & ~1023u;
    const uint32_t sV = sK + HEAD_BYTES;
    unsigned char* sgen = smem_raw + (sK - smem_u32(smem_raw));
    TSTAMP(1, 0);
    const uint32_t bar0 = smem_u32(bars);
    const int wg = threadIdx.x >> 7, warp = (threadIdx.x >> 5) & 3, lane = threadIdx.x & 31, g = lane >> 2, t = lane & 3;
    if (threadIdx.x == 0) {
        for (int i = 0; i < 16; i++) mbar_init(bar0 + 8 * i, 1);
        asm volatile("fence.mbarrier_init.release.cluster;" ::: "memory");
    }
    __syncthreads();
    pdl_launch();
    const uint32_t kd0 = (sK >> 4) | (8u << 16);
    const uint32_t kd1 = ((sK + 256) >> 4);
    const uint32_t khi = 24;
    const uint32_t vd0 = (sV >> 4) | (24u << 16);
    const uint32_t vhi = 8;

    if (blockIdx.x < 4) {
        const int hb = blockIdx.x * 8 + wg * 2;
        const int tid = threadIdx.x & 127;
        {
            if (threadIdx.x < 8) asm volatile("cp.async.bulk.prefetch.L2.global [%0], %1;" :: "l"((const char*)((blockIdx.x & 1) ? woB : woA) + ((blockIdx.x >> 1) * 8 + threadIdx.x) * 41472), "r"(41472) : "memory");
            uint32_t gv[9];
            #pragma unroll
            for (int i = 0; i < 9; i++) gv[i] = ((const uint32_t*)gate_w)[lane + 32 * i];
            #pragma unroll 1
            for (int r = blockIdx.x * 512 + (threadIdx.x >> 5) * 8; r < blockIdx.x * 512 + 512; r += 128) {
                uint32_t xv[8][9];
                #pragma unroll
                for (int q = 0; q < 8; q++) {
                    #pragma unroll
                    for (int i = 0; i < 9; i++) xv[q][i] = ((const uint32_t*)(x + (size_t)(r + q) * DM))[lane + 32 * i];
                }
                float sum[8];
                #pragma unroll
                for (int q = 0; q < 8; q++) {
                    sum[q] = 0.f;
                    #pragma unroll
                    for (int i = 0; i < 9; i++) sum[q] += bfr(bf_lo(xv[q][i]) * bf_lo(gv[i])) + bfr(bf_hi(xv[q][i]) * bf_hi(gv[i]));
                }
                #pragma unroll
                for (int o = 16; o > 0; o >>= 1) {
                    #pragma unroll
                    for (int q = 0; q < 8; q++) sum[q] += __shfl_xor_sync(~0u, sum[q], o);
                }
                float z = sum[0];
                #pragma unroll
                for (int q = 1; q < 8; q++) z = lane == q ? sum[q] : z;
                if (lane < 8) g_gate[r + lane] = bfr(1.0f / (1.0f + __expf(-bfr(z))));
            }
        }
        TSTAMP(1, 3);
        pdl_wait();
        TSTAMP(1, 1);
        const uint32_t slot0 = sK + wg * 49152, fb0 = bar0 + wg * 16;
        auto issue = [&](int c) {
            mbar_expect_tx(fb0 + 8 * (c & 1), 24576);
            bulk_g2s(slot0 + (c & 1) * 24576, (const char*)(g_T + (size_t)(NH + 2 * hb) * HEAD_ELEMS) + (size_t)c * 24576, 24576, fb0 + 8 * (c & 1));
        };
        if (tid == 0) { issue(0); issue(1); }
        #pragma unroll 1
        for (int hi = 0; hi < 2; hi++) {
            float d1[4][12];
            #pragma unroll
            for (int k = 0; k < 4; k++) {
                #pragma unroll
                for (int i = 0; i < 12; i++) d1[k][i] = 0.f;
                fence_regs(d1[k]);
            }
            #pragma unroll 1
            for (int cc = 0; cc < 8; cc++) {
                const int c = hi * 8 + cc;
                mbar_wait_w(fb0 + 8 * (c & 1), (c >> 1) & 1);
                const uint32_t base = ((slot0 + (c & 1) * 24576) >> 4) | (24u << 16);
                WG_FENCE();
                #pragma unroll
                for (int ks = 0; ks < 16; ks++)
                    wgmma_n24_ss<1, 1>(d1[ks & 3], mkdesc(base + ks * 48, 8u), mkdesc(base + 768 + ks * 48, vhi), 1);
                WG_COMMIT();
                WG_WAIT(0);
                named_bar(1 + wg, 128);
                if (tid == 0 && c + 2 < 16) issue(c + 2);
            }
            #pragma unroll
            for (int k = 0; k < 4; k++) fence_regs(d1[k]);
            #pragma unroll
            for (int i = 0; i < 12; i++) d1[0][i] = (d1[0][i] + d1[1][i]) + (d1[2][i] + d1[3][i]);
            if (warp < 2) {
                const int d = warp * 16 + g;
                uint32_t* kp = (uint32_t*)(g_kv + (hb + hi) * 768 + (d >> 3) * 192 + (d & 7) * 8 + 2 * t);
                #pragma unroll
                for (int j = 0; j < 3; j++) {
                    kp[32 * j] = d < 18 ? pack_bf16(d1[0][4 * j], d1[0][4 * j + 1]) : 0u;
                    kp[96 + 32 * j] = warp == 0 ? pack_bf16(d1[0][4 * j + 2], d1[0][4 * j + 3]) : 0u;
                }
                __threadfence();
            }
            named_bar(1 + wg, 128);
            if (tid == 0) asm volatile("st.release.gpu.global.b32 [%0], %1;" :: "l"(g_kvflag + hb + hi), "r"(1) : "memory");
        }
        TSTAMP(1, 4);
        TSTAMP(1, 2);
        return;
    }
    const int cta = blockIdx.x - 4;

    {
        uint4 wv[2];
        #pragma unroll
        for (int q = 0; q < 2; q++) {
            const int id = cta * 648 + threadIdx.x + q * 512;
            if (threadIdx.x + q * 512 < 648) wv[q] = *(const uint4*)((id >= 41472 ? woB - 41472 * 8 : woA) + (size_t)id * 8);
        }
        #pragma unroll
        for (int q = 0; q < 2; q++) {
            const int id = cta * 648 + threadIdx.x + q * 512;
            const int b = id >= 41472, r2 = id - b * 41472, k = r2 / 72, c = r2 % 72;
            const int hh = k / 18, d = k % 18;
            const int kp = (hh >> 2) * 72 + (d < 16 ? (hh & 3) * 16 + d : 64 + (hh & 3) * 2 + (d - 16));
            if (threadIdx.x + q * 512 < 648) *(uint4*)(g_Wt + ((((c / 12) * 2 + b) * 4 + kp / 144) * 12 + (c % 12)) * 1152 + (kp % 144) * 8) = wv[q];
        }
    }

    const int h = cta >> 2, quarter = cta & 3;
    const uint32_t sPQ = sK + 2 * HEAD_BYTES, sKVt = sPQ + 24576;
    pdl_wait();
    TSTAMP(1, 1);
    auto issue_kv = [&](int c) {
        mbar_expect_tx(bar0 + 8 * c, 24576);
        bulk_g2s(sK + c * 12288, (const char*)(g_T + (size_t)(4 * NH + h) * HEAD_ELEMS) + c * 12288, 12288, bar0 + 8 * c);
        bulk_g2s(sV + c * 12288, (const char*)(g_T + (size_t)(5 * NH + h) * HEAD_ELEMS) + c * 12288, 12288, bar0 + 8 * c);
    };
    int kv_state = 0;
    auto kv_poll = [&](bool block) {
        if (threadIdx.x == 0 && kv_state != 2) {
            while (block && kv_state == 0) asm volatile("ld.acquire.gpu.global.b32 %0, [%1];" : "=r"(kv_state) : "l"(g_kvflag + h) : "memory");
            if (kv_state == 1) {
                asm volatile("fence.proxy.async.global;" ::: "memory");
                mbar_expect_tx(bar0 + 72, 1536);
                bulk_g2s(sKVt, g_kv + h * 768, 1536, bar0 + 72);
                kv_state = 2;
            } else {
                asm volatile("ld.acquire.gpu.global.b32 %0, [%1];" : "=r"(kv_state) : "l"(g_kvflag + h) : "memory");
            }
        }
    };
    float km2 = 0.f;
    #pragma unroll
    for (int i = 0; i < 8; i++) km2 = fmaxf(km2, g_kmax[i][h]);
    int s_fast_tmp = 0;
    uint32_t zr = 0u;
    asm volatile("" : "+r"(zr));
    uint32_t qf[2][6];
    #pragma unroll
    for (int pass = 0; pass < 2; pass++) {
        const int row0 = quarter * 512 + (wg * 2 + pass) * 64 + warp * 16 + g;
        const uint32_t* q0 = (const uint32_t*)(g_T + (size_t)(3 * NH + h) * HEAD_ELEMS + (row0 >> 3) * 192 + (row0 & 7) * 8) + t;
        qf[pass][0] = q0[0]; qf[pass][1] = q0[96]; qf[pass][2] = q0[32]; qf[pass][3] = q0[128];
        qf[pass][4] = q0[64]; qf[pass][5] = q0[160];
    }
    if (threadIdx.x == 0) issue_kv(0);
    if (threadIdx.x == 128) issue_kv(1);
    __syncwarp();
    #pragma unroll
    for (int i = 0; i < 6; i++) { qf[0][i] = qscale_pair(qf[0][i]); qf[1][i] = qscale_pair(qf[1][i]); }
    float mrow[2][2];
    bool ok = true;
    #pragma unroll
    for (int pass = 0; pass < 2; pass++) {
        auto sq = [](uint32_t v) { float a = bf_lo(v), b = bf_hi(v); return a * a + b * b; };
        float n0 = sq(qf[pass][0]) + sq(qf[pass][2]) + sq(qf[pass][4]);
        float n1 = sq(qf[pass][1]) + sq(qf[pass][3]) + sq(qf[pass][5]);
        n0 += __shfl_xor_sync(~0u, n0, 1); n0 += __shfl_xor_sync(~0u, n0, 2);
        n1 += __shfl_xor_sync(~0u, n1, 1); n1 += __shfl_xor_sync(~0u, n1, 2);
        mrow[pass][0] = sqrtf(n0 * km2) * 1.01f + 0.01f;
        mrow[pass][1] = sqrtf(n1 * km2) * 1.01f + 0.01f;
        ok = ok && (mrow[pass][0] <= 31.0f) && (mrow[pass][1] <= 31.0f);
    }
    bool fast;
    asm volatile("{\n.reg .pred p, q;\nsetp.ne.b32 p, %1, 0;\nbar.red.and.pred q, %2, 128, p;\nselp.b32 %0, 1, 0, q;\n}\n"
                 : "=r"(*(int*)&s_fast_tmp) : "r"((int)ok), "r"(1 + wg) : "memory");
    fast = __all_sync(0xFFFFFFFFu, s_fast_tmp != 0);
    TSTAMP(1, 3);

    #pragma unroll 1
    for (int pass = 0; pass < 2; pass++) {
        const int row0 = quarter * 512 + (wg * 2 + pass) * 64 + warp * 16 + g;
        uint32_t qa[6];
        #pragma unroll
        for (int i = 0; i < 6; i++) qa[i] = pass ? qf[1][i] : qf[0][i];
        float o[12];
        #pragma unroll
        for (int i = 0; i < 12; i++) o[i] = 0.f;
        fence_regs(o);
        float s[64]; uint32_t p[32];
        #pragma unroll
        for (int i = 0; i < 64; i++) s[i] = 0.f;
        fence_regs(s);
        if (fast) {
            if (t == 1) { qa[4] = pack_bf16(-(pass ? mrow[1][0] : mrow[0][0]), 1.0f); qa[5] = pack_bf16(-(pass ? mrow[1][1] : mrow[0][1]), 1.0f); }
            #pragma unroll 1
            for (int j = 0; j < 16; j++) {
                if (pass == 0 && (j & 1) == 0) {
                    const int cn = (j >> 1) + 2;
                    if ((threadIdx.x & 127) == 0 && (cn & 3) == wg) {
                        if (cn < 8) issue_kv(cn);
                        else if (cn == 8) { mbar_expect_tx(bar0 + 64, 24576); bulk_g2s(sPQ, (const char*)(g_T + (size_t)h * HEAD_ELEMS) + quarter * 24576, 24576, bar0 + 64); }
                    }
                    mbar_wait_w(bar0 + 8 * (j >> 1), 0);
                }
                const uint32_t ko = j * 384;
                WG_FENCE();
                wgmma_n128_rs<0>(s, qa[0], qa[1], qa[2], qa[3], mkdesc(kd0 + ko, khi));
                wgmma_n128_rs<1>(s, qa[4], qa[5], zr, zr, mkdesc(kd1 + ko, khi));
                WG_COMMIT();
                if (pass == 1 && (j & 3) == 3) { kv_poll(false); __syncwarp(); }
                WG_WAIT(0);
                #pragma unroll
                for (int qd = 0; qd < 4; qd++) {
                    if (qd == 0) softmax_blocks<0, 4>(s, p);
                    if (qd == 1) softmax_blocks<4, 4>(s, p);
                    if (qd == 2) softmax_blocks<8, 4>(s, p);
                    if (qd == 3) softmax_blocks<12, 4>(s, p);
                    WG_FENCE();
                    wgmma_n24_rs(o, p[qd * 8 + 0], p[qd * 8 + 1], p[qd * 8 + 2], p[qd * 8 + 3], mkdesc(vd0 + ko + qd * 96, vhi));
                    wgmma_n24_rs(o, p[qd * 8 + 4], p[qd * 8 + 5], p[qd * 8 + 6], p[qd * 8 + 7], mkdesc(vd0 + ko + qd * 96 + 48, vhi));
                    WG_COMMIT();
                }
                WG_WAIT(0);
            }
        } else {
            float mr0 = -INFINITY, mr1 = -INFINITY;
            #pragma unroll 1
            for (int j = 0; j < 16; j++) {
                if (pass == 0 && (j & 1) == 0) {
                    const int cn = (j >> 1) + 2;
                    if ((threadIdx.x & 127) == 0 && (cn & 3) == wg) {
                        if (cn < 8) issue_kv(cn);
                        else if (cn == 8) { mbar_expect_tx(bar0 + 64, 24576); bulk_g2s(sPQ, (const char*)(g_T + (size_t)h * HEAD_ELEMS) + quarter * 24576, 24576, bar0 + 64); }
                    }
                    mbar_wait_w(bar0 + 8 * (j >> 1), 0);
                }
                const uint32_t ko = j * 384;
                WG_FENCE();
                wgmma_n128_rs<0>(s, qa[0], qa[1], qa[2], qa[3], mkdesc(kd0 + ko, khi));
                wgmma_n128_rs<1>(s, qa[4], qa[5], zr, zr, mkdesc(kd1 + ko, khi));
                WG_COMMIT();
                WG_WAIT(0);
                fence_regs(s); fence_regs(o);
                float x0 = mr0, x1 = mr1;
                #pragma unroll
                for (int b = 0; b < 16; b++) {
                    x0 = fmaxf(x0, fmaxf(s[4 * b], s[4 * b + 1]));
                    x1 = fmaxf(x1, fmaxf(s[4 * b + 2], s[4 * b + 3]));
                }
                x0 = fmaxf(x0, __shfl_xor_sync(~0u, x0, 1)); x0 = fmaxf(x0, __shfl_xor_sync(~0u, x0, 2));
                x1 = fmaxf(x1, __shfl_xor_sync(~0u, x1, 1)); x1 = fmaxf(x1, __shfl_xor_sync(~0u, x1, 2));
                const float c0 = exp2f(mr0 - x0), c1 = exp2f(mr1 - x1);
                mr0 = x0; mr1 = x1;
                #pragma unroll
                for (int i = 0; i < 12; i++) o[i] *= (i & 2) ? c1 : c0;
                #pragma unroll
                for (int b = 0; b < 16; b++) {
                    p[2 * b] = pack_bf16(exp2f(s[4 * b] - x0), exp2f(s[4 * b + 1] - x0));
                    p[2 * b + 1] = pack_bf16(exp2f(s[4 * b + 2] - x1), exp2f(s[4 * b + 3] - x1));
                }
                fence_regs(o);
                WG_FENCE();
                #pragma unroll
                for (int kk = 0; kk < 8; kk++)
                    wgmma_n24_rs(o, p[kk * 4 + 0], p[kk * 4 + 1], p[kk * 4 + 2], p[kk * 4 + 3], mkdesc(vd0 + ko + kk * 48, vhi));
                WG_COMMIT();
                WG_WAIT(0);
            }
        }
        fence_regs(o);
        const float l0 = __shfl_sync(~0u, o[8], (lane & ~3) | 1);
        const float l1 = __shfl_sync(~0u, o[10], (lane & ~3) | 1);
        store_o(1, row0, h, t, o, 1.0f / l0, 1.0f / l1);
    }
    TSTAMP(1, 4);
    {
        kv_poll(true); kv_poll(true);
        mbar_wait_w(bar0 + 64, 0);
        phi_inplace<3>(sgen + 2 * HEAD_BYTES + wg * 6144, threadIdx.x & 127);
        named_bar(1 + wg, 128);
        mbar_wait_w(bar0 + 72, 0);
        float e[4][12];
        #pragma unroll
        for (int k = 0; k < 4; k++) {
            #pragma unroll
            for (int i = 0; i < 12; i++) e[k][i] = 0.f;
            fence_regs(e[k]);
        }
        const uint32_t ab = (sPQ + wg * 6144) >> 4, bb = (sKVt >> 4) | (24u << 16);
        WG_FENCE();
        wgmma_n24_ss<0, 1>(e[0], mkdesc(ab | (8u << 16), khi), mkdesc(bb, vhi), 0);
        wgmma_n24_ss<0, 1>(e[1], mkdesc((ab + 192) | (8u << 16), khi), mkdesc(bb, vhi), 0);
        wgmma_n24_ss<0, 1>(e[2], mkdesc(ab + 16, khi), mkdesc(bb + 48, vhi), 0);
        wgmma_n24_ss<0, 1>(e[3], mkdesc(ab + 192 + 16, khi), mkdesc(bb + 48, vhi), 0);
        WG_COMMIT();
        WG_WAIT(0);
        #pragma unroll
        for (int k = 0; k < 4; k++) fence_regs(e[k]);
        #pragma unroll
        for (int m = 0; m < 2; m++) {
            #pragma unroll
            for (int i = 0; i < 12; i++) e[m][i] = bfr(e[m][i] + e[m + 2][i]);
            const float l0 = __shfl_sync(~0u, e[m][8], (lane & ~3) | 1), l1 = __shfl_sync(~0u, e[m][10], (lane & ~3) | 1);
            store_o(0, quarter * 512 + (wg * 2 + m) * 64 + warp * 16 + g, h, t, e[m], 1.0f / bfr(l0 + 1e-6f), 1.0f / bfr(l1 + 1e-6f));
        }
    }
    TSTAMP(1, 2);
}

#define K3_STAGES 3
#define K3_STAGE_BYTES 64512
#define K3_SMEM (K3_STAGES * K3_STAGE_BYTES + 1024)
#define K3_CL 3

__global__ void __cluster_dims__(K3_CL, 1, 1) __launch_bounds__(288, 1)
out_kernel(__nv_bfloat16* __restrict__ out) {
    extern __shared__ unsigned char smem_raw[];
    __shared__ __align__(8) uint64_t bars[2 * K3_STAGES];
    const uint32_t sA = (smem_u32(smem_raw) + 1023u) & ~1023u;
    const uint32_t full0 = smem_u32(bars), empty0 = full0 + 8 * K3_STAGES;
    const int mt = blockIdx.x / 6, nt = blockIdx.x % 6, rank = nt % K3_CL;
    const int m0 = mt * 128, n0 = nt * 96;
    TSTAMP(2, 0);
    if (threadIdx.x == 0) {
        for (int i = 0; i < K3_STAGES; i++) { mbar_init(full0 + 8 * i, 1); mbar_init(empty0 + 8 * i, 2 * K3_CL); }
        asm volatile("fence.mbarrier_init.release.cluster;" ::: "memory");
    }
    __syncwarp();
    cluster_sync();
    TSTAMP(2, 3);
    pdl_wait();
    TSTAMP(2, 1);
    const int wg = threadIdx.x >> 7;
    if (wg == 2) {
        if (threadIdx.x == 256) {
            for (int c = 0; c < 8; c++) {
                const int s = c % K3_STAGES;
                if (c >= K3_STAGES) mbar_wait(empty0 + 8 * s, ((c / K3_STAGES) - 1) & 1);
                const uint32_t st = sA + s * K3_STAGE_BYTES;
                mbar_expect_tx(full0 + 8 * s, K3_STAGE_BYTES);
                const char* asrc = (const char*)(g_O + (size_t)(((c & 1) * 16 + mt) * 8 + 2 * (c >> 1)) * 9216) + rank * (36864 / K3_CL);
                asm volatile("cp.async.bulk.shared::cluster.global.mbarrier::complete_tx::bytes.multicast::cluster [%0], [%1], %2, [%3], %4;"
                             :: "r"(st + rank * (36864 / K3_CL)), "l"(asrc), "r"(36864 / K3_CL), "r"(full0 + 8 * s), "h"((uint16_t)((1 << K3_CL) - 1)) : "memory");
                bulk_g2s(st + 36864, g_Wt + (size_t)(nt * 8 + (c & 1) * 4 + (c >> 1)) * 13824, 27648, full0 + 8 * s);
            }
        }
        __syncwarp();
    } else {
        const int warp = (threadIdx.x >> 5) & 3, lane = threadIdx.x & 31, g = lane >> 2, t = lane & 3;
        float aa[48], ab[48];
        #pragma unroll
        for (int i = 0; i < 48; i++) { aa[i] = 0.f; ab[i] = 0.f; }
        fence_regs(aa); fence_regs(ab);
        const uint32_t hiA = 72u;
        const uint32_t hiB = 144u;
        const int r0 = m0 + wg * 64 + warp * 16 + g;
        const float g0 = g_gate[r0], g1 = g_gate[r0 + 8];
        auto stage = [&](int c, float (&acc)[48]) {
            const int s = c % K3_STAGES;
            mbar_wait_w(full0 + 8 * s, (c / K3_STAGES) & 1);
            const uint32_t a_lo = ((sA + s * K3_STAGE_BYTES + wg * 9216) & 0x3FFFF) >> 4;
            const uint32_t b_lo = (((sA + s * K3_STAGE_BYTES + 36864) & 0x3FFFF) >> 4) | (8u << 16);
            WG_FENCE();
            #pragma unroll
            for (int i = 0; i < 9; i++) {
                const uint32_t ad = i < 4 ? (a_lo + i * 16) | (8u << 16) : i == 4 ? (a_lo + 64) | (1088u << 16) : (a_lo + 1152 + 8 + (i - 5) * 16) | (8u << 16);
                wgmma_n96_ss(acc, mkdesc(ad, hiA), mkdesc(b_lo + i * 16, hiB));
            }
            WG_COMMIT();
            WG_WAIT(1);
            if (c > 0 && c - 1 + K3_STAGES < 8 && (threadIdx.x & 127) < K3_CL) mbar_arrive_cta(empty0 + 8 * ((c - 1) % K3_STAGES), threadIdx.x & 127);
        };
        #pragma unroll 1
        for (int pr = 0; pr < 4; pr++) {
            stage(2 * pr, aa);
            if (pr == 0) TSTAMP(2, 4);
            stage(2 * pr + 1, ab);
        }
        WG_WAIT(0);
        fence_regs(aa); fence_regs(ab);
        TSTAMP(2, 5);
        const float h0 = bfr(1.0f - g0), h1 = bfr(1.0f - g1);
        named_bar(1, 256);
        const uint32_t stw = sA + K3_STAGE_BYTES * 2 + (wg * 4 + warp) * 3328;
        #pragma unroll
        for (int j = 0; j < 12; j++) {
            float v0 = bfr(g0 * bfr(aa[4 * j])) + bfr(h0 * bfr(ab[4 * j]));
            float v1 = bfr(g0 * bfr(aa[4 * j + 1])) + bfr(h0 * bfr(ab[4 * j + 1]));
            float v2 = bfr(g1 * bfr(aa[4 * j + 2])) + bfr(h1 * bfr(ab[4 * j + 2]));
            float v3 = bfr(g1 * bfr(aa[4 * j + 3])) + bfr(h1 * bfr(ab[4 * j + 3]));
            sts32(stw + g * 208 + j * 16 + t * 4, pack_bf16(v0, v1));
            sts32(stw + (g + 8) * 208 + j * 16 + t * 4, pack_bf16(v2, v3));
        }
        __syncwarp();
        #pragma unroll
        for (int i = 0; i < 6; i++) {
            const int id = i * 32 + lane, r = id / 12, c = id % 12;
            uint4 v;
            asm volatile("ld.shared.v4.b32 {%0,%1,%2,%3}, [%4];" : "=r"(v.x), "=r"(v.y), "=r"(v.z), "=r"(v.w) : "r"(stw + r * 208 + c * 16));
            *(uint4*)(out + (size_t)(m0 + wg * 64 + warp * 16 + r) * DM + n0 + c * 8) = v;
        }
        TSTAMP(2, 2);
    }
    cluster_sync();
}

typedef CUresult (*EncodeFn)(CUtensorMap*, CUtensorMapDataType, cuuint32_t, void*, const cuuint64_t*, const cuuint64_t*,
                             const cuuint32_t*, const cuuint32_t*, CUtensorMapInterleave, CUtensorMapSwizzle,
                             CUtensorMapL2promotion, CUtensorMapFloatOOBfill);

static void make_map(EncodeFn enc, CUtensorMap* m, const void* base, uint64_t inner, uint64_t outer, uint32_t box_in, uint32_t box_out, CUtensorMapSwizzle sw) {
    cuuint64_t dims[2] = {inner, outer};
    cuuint64_t strides[1] = {inner * 2};
    cuuint32_t box[2] = {box_in, box_out};
    cuuint32_t es[2] = {1, 1};
    enc(m, CU_TENSOR_MAP_DATA_TYPE_BFLOAT16, 2, (void*)base, dims, strides, box, es, CU_TENSOR_MAP_INTERLEAVE_NONE, sw,
        CU_TENSOR_MAP_L2_PROMOTION_L2_256B, CU_TENSOR_MAP_FLOAT_OOB_FILL_NONE);
}

extern "C" void kernel_launch(void* const* d_in, const int* in_sizes, int n_in, void* d_out, int out_size) {
    const __nv_bfloat16* x = (const __nv_bfloat16*)d_in[0];
    const __nv_bfloat16* wA = (const __nv_bfloat16*)d_in[1];
    const __nv_bfloat16* woA = (const __nv_bfloat16*)d_in[2];
    const __nv_bfloat16* wB = (const __nv_bfloat16*)d_in[4];
    const __nv_bfloat16* woB = (const __nv_bfloat16*)d_in[5];
    const __nv_bfloat16* gw = (const __nv_bfloat16*)d_in[6];
    __nv_bfloat16* out = (__nv_bfloat16*)d_out;

    static EncodeFn enc = nullptr;
    if (!enc) {
        void* fn = nullptr; cudaDriverEntryPointQueryResult st;
        cudaGetDriverEntryPoint("cuTensorMapEncodeTiled", &fn, cudaEnableDefault, &st);
        enc = (EncodeFn)fn;
        cudaFuncSetAttribute(qkv_kernel, cudaFuncAttributeMaxDynamicSharedMemorySize, K1_SMEM);
        cudaFuncSetAttribute(attn_kernel, cudaFuncAttributeMaxDynamicSharedMemorySize, K2_SMEM);
        cudaFuncSetAttribute(out_kernel, cudaFuncAttributeMaxDynamicSharedMemorySize, K3_SMEM);
    }
    CUtensorMap mX, mWA, mWA2, mWB, mWB2;
    make_map(enc, &mX, x, DM, S_LEN, 64, 256, CU_TENSOR_MAP_SWIZZLE_128B);
    make_map(enc, &mWA, wA, 3 * DM, DM, 64, 64, CU_TENSOR_MAP_SWIZZLE_128B);
    make_map(enc, &mWA2, wA, 3 * DM, DM, 32, 64, CU_TENSOR_MAP_SWIZZLE_64B);
    make_map(enc, &mWB, wB, 3 * DM, DM, 64, 64, CU_TENSOR_MAP_SWIZZLE_128B);
    make_map(enc, &mWB2, wB, 3 * DM, DM, 32, 64, CU_TENSOR_MAP_SWIZZLE_64B);

    cudaStream_t stream = cudaStreamPerThread;
    cudaLaunchAttribute at[1];
    at[0].id = cudaLaunchAttributeProgrammaticStreamSerialization;
    at[0].val.programmaticStreamSerializationAllowed = 1;

    qkv_kernel<<<128, 256, K1_SMEM, stream>>>(mX, mWA, mWA2, mWB, mWB2);

    cudaLaunchConfig_t c2 = {};
    c2.gridDim = dim3(132); c2.blockDim = dim3(512); c2.dynamicSmemBytes = K2_SMEM; c2.stream = stream; c2.attrs = at; c2.numAttrs = 1;
    cudaLaunchKernelEx(&c2, attn_kernel, x, gw, woA, woB);

    cudaLaunchConfig_t c3 = {};
    c3.gridDim = dim3(96); c3.blockDim = dim3(288); c3.dynamicSmemBytes = K3_SMEM; c3.stream = stream; c3.attrs = at; c3.numAttrs = 1;
    cudaLaunchKernelEx(&c3, out_kernel, out);
}
```

```cpp
#include <cuda_runtime.h>
#include <cuda_bf16.h>
#include <cuda.h>
#include <stdint.h>

#define S_LEN 2048
#define DM 576
#define NH 32
#define DH 18
#define HEAD_ELEMS 49152
#define HEAD_BYTES 98304

#define POLY_BLK 0xAAAA

__device__ __align__(1024) __nv_bfloat16 g_T[6 * NH * HEAD_ELEMS];
__device__ float g_kmax[8][NH];
__device__ __align__(1024) __nv_bfloat16 g_O[2 * S_LEN * DM];
__device__ float g_gate[S_LEN];
__device__ __align__(128) __nv_bfloat16 g_kv[NH * 768];
__device__ int g_kvflag[NH];
__device__ __align__(1024) __nv_bfloat16 g_Wt[3 * 2 * 8 * 13824];

#define TSTAMP(k, i)
#define WG_FENCE() asm volatile("wgmma.fence.sync.aligned;\n" ::: "memory")
#define WG_COMMIT() asm volatile("wgmma.commit_group.sync.aligned;\n" ::: "memory")
#define WG_WAIT(n) asm volatile("wgmma.wait_group.sync.aligned %0;\n" :: "n"(n) : "memory")

__device__ __forceinline__ uint64_t mkdesc(uint32_t lo, uint32_t hi) {
    uint64_t d; asm("mov.b64 %0, {%1, %2};" : "=l"(d) : "r"(lo), "r"(hi)); return d;
}
__device__ __forceinline__ uint32_t smem_u32(const void* p) { return (uint32_t)__cvta_generic_to_shared(p); }
__device__ __forceinline__ void mbar_init(uint32_t bar, uint32_t cnt) { asm volatile("mbarrier.init.shared::cta.b64 [%0], %1;" :: "r"(bar), "r"(cnt)); }
__device__ __forceinline__ void mbar_expect_tx(uint32_t bar, uint32_t bytes) { asm volatile("mbarrier.arrive.expect_tx.shared::cta.b64 _, [%0], %1;" :: "r"(bar), "r"(bytes) : "memory"); }
__device__ __forceinline__ void mbar_arrive(uint32_t bar) { asm volatile("mbarrier.arrive.shared::cta.b64 _, [%0];" :: "r"(bar) : "memory"); }
__device__ __forceinline__ void mbar_wait(uint32_t bar, uint32_t parity) {
    asm volatile("{\n.reg .pred p;\nWAIT_%=:\nmbarrier.try_wait.parity.shared::cta.b64 p, [%0], %1;\n@p bra DONE_%=;\nbra WAIT_%=;\nDONE_%=:\n}\n" :: "r"(bar), "r"(parity) : "memory");
}
__device__ __forceinline__ void mbar_wait_w(uint32_t bar, uint32_t parity) { __syncwarp(); mbar_wait(bar, parity); }
__device__ __forceinline__ void bulk_g2s(uint32_t dst, const void* src, uint32_t bytes, uint32_t bar) {
    asm volatile("cp.async.bulk.shared::cluster.global.mbarrier::complete_tx::bytes [%0], [%1], %2, [%3];" :: "r"(dst), "l"(src), "r"(bytes), "r"(bar) : "memory");
}
__device__ __forceinline__ void tma_2d(uint32_t dst, const CUtensorMap* map, int c0, int c1, uint32_t bar) {
    asm volatile("cp.async.bulk.tensor.2d.shared::cluster.global.mbarrier::complete_tx::bytes [%0], [%1, {%3, %4}], [%2];"
                 :: "r"(dst), "l"((uint64_t)map), "r"(bar), "r"(c0), "r"(c1) : "memory");
}
__device__ __forceinline__ void tma_3d(uint32_t dst, const CUtensorMap* map, int c0, int c1, int c2, uint32_t bar) {
    asm volatile("cp.async.bulk.tensor.3d.shared::cluster.global.mbarrier::complete_tx::bytes [%0], [%1, {%3, %4, %5}], [%2];"
                 :: "r"(dst), "l"((uint64_t)map), "r"(bar), "r"(c0), "r"(c1), "r"(c2) : "memory");
}
__device__ __forceinline__ void cluster_arrive() { asm volatile("barrier.cluster.arrive.release.aligned;" ::: "memory"); }
__device__ __forceinline__ void cluster_wait() { asm volatile("barrier.cluster.wait.acquire.aligned;" ::: "memory"); }
__device__ __forceinline__ void cluster_sync() { cluster_arrive(); cluster_wait(); }
__device__ __forceinline__ void mbar_arrive_cta(uint32_t bar, uint32_t cta) {
    uint32_t ra;
    asm volatile("mapa.shared::cluster.u32 %0, %1, %2;" : "=r"(ra) : "r"(bar), "r"(cta));
    asm volatile("mbarrier.arrive.release.cluster.shared::cluster.b64 _, [%0];" :: "r"(ra) : "memory");
}
__device__ __forceinline__ void named_bar(int id, int n) { asm volatile("bar.sync %0, %1;" :: "r"(id), "r"(n) : "memory"); }
__device__ __forceinline__ void fence_async() { asm volatile("fence.proxy.async.shared::cta;" ::: "memory"); }
__device__ __forceinline__ void pdl_wait() { asm volatile("griddepcontrol.wait;" ::: "memory"); }
__device__ __forceinline__ void pdl_launch() { asm volatile("griddepcontrol.launch_dependents;" ::: "memory"); }

__device__ __forceinline__ float ex2f(float x) { float y; asm("ex2.approx.ftz.f32 %0, %1;" : "=f"(y) : "f"(x)); return y; }
__device__ __forceinline__ uint32_t pack_bf16(float lo, float hi) { uint32_t r; asm("cvt.rn.bf16x2.f32 %0, %1, %2;" : "=r"(r) : "f"(hi), "f"(lo)); return r; }
__device__ __forceinline__ float bf_lo(uint32_t v) { return __uint_as_float(v << 16); }
__device__ __forceinline__ float bf_hi(uint32_t v) { return __uint_as_float(v & 0xFFFF0000u); }
__device__ __forceinline__ float bfr(float x) { return __uint_as_float(pack_bf16(0.f, x) & 0xFFFF0000u); }

#define ACC4(a, o) "+f"(a[o]), "+f"(a[o + 1]), "+f"(a[o + 2]), "+f"(a[o + 3])
#define ACC12(a, o) ACC4(a, o), ACC4(a, o + 4), ACC4(a, o + 8)
#define ACC16(a, o) ACC4(a, o), ACC4(a, o + 4), ACC4(a, o + 8), ACC4(a, o + 12)
#define ACC32(a, o) ACC16(a, o), ACC16(a, o + 16)

__device__ __forceinline__ void wgmma_n24_rs(float (&d)[12], uint32_t a0, uint32_t a1, uint32_t a2, uint32_t a3, uint64_t bdesc) {
    asm volatile("{\n.reg .pred p;\nsetp.ne.b32 p, 1, 0;\n"
        "wgmma.mma_async.sync.aligned.m64n24k16.f32.bf16.bf16 "
        "{%0,%1,%2,%3,%4,%5,%6,%7,%8,%9,%10,%11}, {%12,%13,%14,%15}, %16, p, 1, 1, 1;\n}\n"
        : ACC12(d, 0) : "r"(a0), "r"(a1), "r"(a2), "r"(a3), "l"(bdesc));
}
template<int TA, int TB>
__device__ __forceinline__ void wgmma_n24_ss(float (&d)[12], uint64_t adesc, uint64_t bdesc, int acc) {
    asm volatile("{\n.reg .pred p;\nsetp.ne.b32 p, %14, 0;\n"
        "wgmma.mma_async.sync.aligned.m64n24k16.f32.bf16.bf16 "
        "{%0,%1,%2,%3,%4,%5,%6,%7,%8,%9,%10,%11}, %12, %13, p, 1, 1, %15, %16;\n}\n"
        : ACC12(d, 0) : "l"(adesc), "l"(bdesc), "r"(acc), "n"(TA), "n"(TB));
}
template<int ACC>
__device__ __forceinline__ void wgmma_n128_rs(float (&d)[64], uint32_t a0, uint32_t a1, uint32_t a2, uint32_t a3, uint64_t bdesc) {
    asm volatile("{\n.reg .pred p;\nsetp.ne.b32 p, %69, 0;\n"
        "wgmma.mma_async.sync.aligned.m64n128k16.f32.bf16.bf16 "
        "{%0,%1,%2,%3,%4,%5,%6,%7,%8,%9,%10,%11,%12,%13,%14,%15,%16,%17,%18,%19,%20,%21,%22,%23,%24,%25,%26,%27,%28,%29,%30,%31,"
        "%32,%33,%34,%35,%36,%37,%38,%39,%40,%41,%42,%43,%44,%45,%46,%47,%48,%49,%50,%51,%52,%53,%54,%55,%56,%57,%58,%59,%60,%61,%62,%63}, {%64,%65,%66,%67}, %68, p, 1, 1, 0;\n}\n"
        : ACC32(d, 0), ACC32(d, 32) : "r"(a0), "r"(a1), "r"(a2), "r"(a3), "l"(bdesc), "n"(ACC));
}
__device__ __forceinline__ void wgmma_n192_ss(float (&d)[96], uint64_t adesc, uint64_t bdesc, int acc) {
    asm volatile("{\n.reg .pred p;\nsetp.ne.b32 p, %98, 0;\n"
        "wgmma.mma_async.sync.aligned.m64n192k16.f32.bf16.bf16 "
        "{%0,%1,%2,%3,%4,%5,%6,%7,%8,%9,%10,%11,%12,%13,%14,%15,%16,%17,%18,%19,%20,%21,%22,%23,%24,%25,%26,%27,%28,%29,%30,%31,"
        "%32,%33,%34,%35,%36,%37,%38,%39,%40,%41,%42,%43,%44,%45,%46,%47,%48,%49,%50,%51,%52,%53,%54,%55,%56,%57,%58,%59,%60,%61,%62,%63,"
        "%64,%65,%66,%67,%68,%69,%70,%71,%72,%73,%74,%75,%76,%77,%78,%79,%80,%81,%82,%83,%84,%85,%86,%87,%88,%89,%90,%91,%92,%93,%94,%95}, %96, %97, p, 1, 1, 0, 1;\n}\n"
        : ACC32(d, 0), ACC32(d, 32), ACC32(d, 64) : "l"(adesc), "l"(bdesc), "r"(acc));
}
__device__ __forceinline__ void wgmma_n96_ss(float (&d)[48], uint64_t adesc, uint64_t bdesc) {
    asm volatile("{\n.reg .pred p;\nsetp.ne.b32 p, 1, 0;\n"
        "wgmma.mma_async.sync.aligned.m64n96k16.f32.bf16.bf16 "
        "{%0,%1,%2,%3,%4,%5,%6,%7,%8,%9,%10,%11,%12,%13,%14,%15,%16,%17,%18,%19,%20,%21,%22,%23,%24,%25,%26,%27,%28,%29,%30,%31,%32,%33,%34,%35,%36,%37,%38,%39,%40,%41,%42,%43,%44,%45,%46,%47}, %48, %49, p, 1, 1, 0, 1;\n}\n"
        : ACC32(d, 0), ACC16(d, 32) : "l"(adesc), "l"(bdesc));
}
template<int N> __device__ __forceinline__ void fence_regs(float (&d)[N]) {
    #pragma unroll
    for (int i = 0; i < N; i++) asm volatile("" : "+f"(d[i]) :: "memory");
}

#define K1_STAGES 3
#define K1_STAGE_BYTES 61440
#define K1_SMEM (K1_STAGES * K1_STAGE_BYTES + 1024)
#define K1_STORE_BYTES 12288

__device__ __forceinline__ uint32_t hadd2_bf16(uint32_t a, uint32_t b) { uint32_t r; asm("add.rn.bf16x2 %0, %1, %2;" : "=r"(r) : "r"(a), "r"(b)); return r; }
__device__ __forceinline__ uint32_t phi_pair(uint32_t w) {
    const uint32_t p1 = hadd2_bf16(w, 0x3F803F80u);
    const uint32_t pe = pack_bf16(ex2f(bf_lo(w) * 1.4426950408889634f), ex2f(bf_hi(w) * 1.4426950408889634f));
    uint32_t m; asm("prmt.b32 %0, %1, 0, 0xBB99;" : "=r"(m) : "r"(w));
    const uint32_t r = (pe & m) | (p1 & ~m);
    return pack_bf16(bf_lo(r) + 1e-6f, bf_hi(r) + 1e-6f);
}
template<int N> __device__ __forceinline__ void phi_inplace(unsigned char* p, int tid) {
    uint4 v[N];
    #pragma unroll
    for (int i = 0; i < N; i++) v[i] = *(uint4*)(p + (i * 128 + tid) * 16);
    #pragma unroll
    for (int i = 0; i < N; i++) {
        v[i].x = phi_pair(v[i].x); v[i].y = phi_pair(v[i].y); v[i].z = phi_pair(v[i].z); v[i].w = phi_pair(v[i].w);
        *(uint4*)(p + (i * 128 + tid) * 16) = v[i];
    }
    fence_async();
}
__device__ __forceinline__ void phi36(uint32_t (&w)[36]) {
    #pragma unroll
    for (int i = 0; i < 36; i++) w[i] = phi_pair(w[i]);
}
__device__ __forceinline__ uint32_t qscale_pair(uint32_t w) {
    const float qs = 0.23570226039551584f * 1.4426950408889634f;
    return pack_bf16(bf_lo(w) * qs, bf_hi(w) * qs);
}
__device__ __forceinline__ void sts32(uint32_t addr, uint32_t v) { asm volatile("st.shared.b32 [%0], %1;" :: "r"(addr), "r"(v) : "memory"); }

__global__ void __launch_bounds__(256, 1)
qkv_kernel(const __grid_constant__ CUtensorMap mapX, const __grid_constant__ CUtensorMap mapWA, const __grid_constant__ CUtensorMap mapWA2,
           const __grid_constant__ CUtensorMap mapWB, const __grid_constant__ CUtensorMap mapWB2) {
    extern __shared__ unsigned char smem_raw[];
    __shared__ __align__(8) uint64_t bars[2 * K1_STAGES];
    __shared__ uint32_t s_nmax[12];
    const uint32_t sbase = (smem_u32(smem_raw) + 1023u) & ~1023u;
    unsigned char* stg = smem_raw + (sbase - smem_u32(smem_raw));
    const uint32_t full0 = smem_u32(bars), empty0 = full0 + 8 * K1_STAGES;
    const int mt = blockIdx.x >> 4, nt = blockIdx.x & 15;
    const int branch = nt >> 3, n0 = (nt & 7) * 216, m0 = mt * 256;
    const int wg = threadIdx.x >> 7;
    const int warp = (threadIdx.x >> 5) & 3, lane = threadIdx.x & 31, g = lane >> 2, t = lane & 3;
    TSTAMP(0, 0);
    const CUtensorMap* w1 = branch ? &mapWB : &mapWA;
    const CUtensorMap* w2 = branch ? &mapWB2 : &mapWA2;
    auto issue = [&](int kt, int part) {
        const int s = kt % K1_STAGES;
        const uint32_t st = sbase + s * K1_STAGE_BYTES, fb = full0 + 8 * s;
        if (part == 0) {
            mbar_expect_tx(fb, K1_STAGE_BYTES);
            tma_2d(st, &mapX, kt * 64, m0, fb);
            tma_2d(st + 32768 + 24576, w2, n0 + 192, kt * 64, fb);
        } else {
            tma_2d(st + 32768, w1, n0, kt * 64, fb);
            tma_2d(st + 32768 + 8192, w1, n0 + 64, kt * 64, fb);
            tma_2d(st + 32768 + 16384, w1, n0 + 128, kt * 64, fb);
        }
    };
    if (threadIdx.x == 0) {
        for (int i = 0; i < K1_STAGES; i++) { mbar_init(full0 + 8 * i, 1); mbar_init(empty0 + 8 * i, 2); }
        asm volatile("fence.mbarrier_init.release.cluster;" ::: "memory");
        issue(0, 0); issue(0, 1);
    }
    if (threadIdx.x >= 64 && threadIdx.x < 76) s_nmax[threadIdx.x - 64] = 0;
    if (blockIdx.x == 0 && threadIdx.x >= 32 && threadIdx.x < 64) g_kvflag[threadIdx.x - 32] = 0;
    __syncthreads();
    if (lane == 0 && threadIdx.x < 128) issue(1 + (threadIdx.x >> 6), (threadIdx.x >> 5) & 1);
    pdl_launch();
    const uint32_t hiA = 64u | 0x40000000u;
    const uint32_t hiB = 64u | 0x40000000u;
    const uint32_t hiB2 = 32u | 0x80000000u;
    float acc0[96], acc1[96], acd0[12], acd1[12];
    #pragma unroll
    for (int i = 0; i < 96; i++) { acc0[i] = 0.f; acc1[i] = 0.f; }
    #pragma unroll
    for (int i = 0; i < 12; i++) { acd0[i] = 0.f; acd1[i] = 0.f; }
    fence_regs(acc0); fence_regs(acc1); fence_regs(acd0); fence_regs(acd1);
    #pragma unroll 1
    for (int kt = 0; kt < 9; kt++) {
        const int s = kt % K1_STAGES;
        mbar_wait_w(full0 + 8 * s, (kt / K1_STAGES) & 1);
        const uint32_t st = sbase + s * K1_STAGE_BYTES;
        const uint32_t a_lo = ((st + wg * 16384) >> 4) | (1u << 16);
        const uint32_t b_lo = ((st + 32768) >> 4) | (512u << 16);
        const uint32_t b2_lo = ((st + 32768 + 24576) >> 4) | (1u << 16);
        WG_FENCE();
        #pragma unroll
        for (int kk = 0; kk < 4; kk++) {
            wgmma_n192_ss(acc0, mkdesc(a_lo + kk * 2, hiA), mkdesc(b_lo + kk * 128, hiB), 1);
            wgmma_n24_ss<0, 1>(acd0, mkdesc(a_lo + kk * 2, hiA), mkdesc(b2_lo + kk * 64, hiB2), 1);
            wgmma_n192_ss(acc1, mkdesc(a_lo + 512 + kk * 2, hiA), mkdesc(b_lo + kk * 128, hiB), 1);
            wgmma_n24_ss<0, 1>(acd1, mkdesc(a_lo + 512 + kk * 2, hiA), mkdesc(b2_lo + kk * 64, hiB2), 1);
        }
        WG_COMMIT();
        WG_WAIT(1);
        if (kt > 0 && kt + 2 < 9) {
            const int sp = (kt - 1) % K1_STAGES;
            if ((threadIdx.x & 127) == 0) mbar_arrive(empty0 + 8 * sp);
            if (threadIdx.x < 32) {
                mbar_wait_w(empty0 + 8 * sp, ((kt - 1) / K1_STAGES) & 1);
                if (lane == 0) { issue(kt + 2, 0); issue(kt + 2, 1); }
            }
            __syncwarp();
        }
    }
    WG_WAIT(0);
    fence_regs(acc0); fence_regs(acc1); fence_regs(acd0); fence_regs(acd1);
    TSTAMP(0, 1);
    __syncthreads();
    {
        uint32_t off9[9];
        #pragma unroll
        for (int jj = 0; jj < 9; jj++) {
            const int c = 8 * jj + 2 * t, hh = c / 18, d = c - hh * 18;
            off9[jj] = hh * 12288 + (d >> 3) * 128 + (d & 7) * 2;
        }
        const uint32_t base = sbase + (wg * 16 + warp * 2) * 384 + g * 16;
        const int k0 = branch * 3 + n0 / 576, k1 = branch * 3 + (n0 + 72) / 576, k2 = branch * 3 + (n0 + 144) / 576;
        const int row = threadIdx.x;
        const uint32_t pmagic = ((POLY_BLK >> ((row & 127) >> 3)) & 1) ? 0x46013F80u : 0x3F803F80u;
        const uint32_t pa = sbase + (row >> 3) * 384 + 256 + (row & 7) * 16 + 4;
        #pragma unroll
        for (int hh = 0; hh < 12; hh++) {
            const int kind = hh < 4 ? k0 : hh < 8 ? k1 : k2;
            sts32(pa + hh * 12288, kind == 4 ? pmagic : (kind == 2 || kind == 5) ? 0x00003F80u : 0u);
            asm volatile("st.shared.v2.b32 [%0], {%1, %1};" :: "r"(pa + hh * 12288 + 4), "r"(0u) : "memory");
        }
        auto flush = [&](int grp) {
            fence_async();
            __syncthreads();
            if (lane == 0 && threadIdx.x < 128) {
                const int hh = grp * 4 + (threadIdx.x >> 5), col0 = n0 + hh * 18;
                const int type = col0 / 576, head = (col0 % 576) / 18, kind = branch * 3 + type;
                const size_t hb = (kind == 1 || kind == 2) ? (size_t)(NH + 2 * head) * HEAD_ELEMS + mt * 12288 + (kind - 1) * 6144
                                                           : (size_t)(kind * NH + head) * HEAD_ELEMS + mt * 6144;
                asm volatile("cp.async.bulk.global.shared::cta.bulk_group [%0], [%1], %2;" :: "l"(g_T + hb), "r"(sbase + hh * 12288), "r"(K1_STORE_BYTES) : "memory");
                asm volatile("cp.async.bulk.commit_group;" ::: "memory");
            }
            __syncwarp();
        };
        #pragma unroll
        for (int grp = 0; grp < 3; grp++) {
            uint32_t w[36];
            #pragma unroll
            for (int jj = 0; jj < 9; jj++) {
                const int j = grp * 9 + jj;
                if (j < 24) {
                    w[4 * jj] = pack_bf16(acc0[(4 * j) % 96], acc0[(4 * j + 1) % 96]); w[4 * jj + 1] = pack_bf16(acc0[(4 * j + 2) % 96], acc0[(4 * j + 3) % 96]);
                    w[4 * jj + 2] = pack_bf16(acc1[(4 * j) % 96], acc1[(4 * j + 1) % 96]); w[4 * jj + 3] = pack_bf16(acc1[(4 * j + 2) % 96], acc1[(4 * j + 3) % 96]);
                } else {
                    w[4 * jj] = pack_bf16(acd0[(4 * j) % 12], acd0[(4 * j + 1) % 12]); w[4 * jj + 1] = pack_bf16(acd0[(4 * j + 2) % 12], acd0[(4 * j + 3) % 12]);
                    w[4 * jj + 2] = pack_bf16(acd1[(4 * j) % 12], acd1[(4 * j + 1) % 12]); w[4 * jj + 3] = pack_bf16(acd1[(4 * j + 2) % 12], acd1[(4 * j + 3) % 12]);
                }
            }
            if ((grp == 0 ? k0 : grp == 1 ? k1 : k2) == 1) phi36(w);
            #pragma unroll
            for (int jj = 0; jj < 9; jj++) {
                const uint32_t a = base + grp * 49152 + off9[jj];
                sts32(a, w[4 * jj]); sts32(a + 384, w[4 * jj + 1]); sts32(a + 3072, w[4 * jj + 2]); sts32(a + 3456, w[4 * jj + 3]);
            }
            flush(grp);
        }
        TSTAMP(0, 3);
        #pragma unroll 1
        for (int grp = 0; grp < 3; grp++) {
            if ((grp == 0 ? k0 : grp == 1 ? k1 : k2) == 4) {
                #pragma unroll 2
                for (int hq = 0; hq < 4; hq++) {
                    const unsigned char* src = stg + (grp * 4 + hq) * 12288 + (row >> 3) * 384 + (row & 7) * 16;
                    const uint4 v0 = *(const uint4*)src, v1 = *(const uint4*)(src + 128);
                    const uint32_t w[9] = {v0.x, v0.y, v0.z, v0.w, v1.x, v1.y, v1.z, v1.w, *(const uint32_t*)(src + 256)};
                    float n2 = 0.f;
                    #pragma unroll
                    for (int i = 0; i < 9; i++) { const float a = bf_lo(w[i]), b = bf_hi(w[i]); n2 = fmaf(a, a, n2); n2 = fmaf(b, b, n2); }
                    uint32_t nb = __float_as_uint(n2);
                    if (!(n2 >= 0.f)) nb = 0x7F800000u;
                    nb = __reduce_max_sync(0xFFFFFFFFu, nb);
                    if (lane == 0) atomicMax(&s_nmax[grp * 4 + hq], nb);
                }
            }
        }
        __syncthreads();
        if (threadIdx.x < 12) {
            const int col0 = n0 + threadIdx.x * 18;
            if (branch == 1 && col0 / 576 == 1) g_kmax[mt][(col0 % 576) / 18] = __uint_as_float(s_nmax[threadIdx.x]);
        }
        if (lane == 0 && threadIdx.x < 128) asm volatile("cp.async.bulk.wait_group.read 0;" ::: "memory");
    }
    TSTAMP(0, 2);
}

__device__ __forceinline__ uint32_t hfma2(uint32_t a, uint32_t b, uint32_t c) { uint32_t r; asm("fma.rn.f16x2 %0, %1, %2, %3;" : "=r"(r) : "r"(a), "r"(b), "r"(c)); return r; }
__device__ __forceinline__ uint32_t and_or(uint32_t a, uint32_t m, uint32_t o) { uint32_t r; asm("lop3.b32 %0, %1, %2, %3, 0xEA;" : "=r"(r) : "r"(a), "r"(m), "r"(o)); return r; }
__device__ __forceinline__ uint32_t poly_ex2_pair(float t0, float t1) {
    const uint32_t u = __byte_perm(__float_as_uint(t0), __float_as_uint(t1), 0x5410);
    const uint32_t m = and_or(u, 0x03FF03FFu, 0x3C003C00u);
    uint32_t y = hfma2(m, 0x2CFE2CFEu, 0xA019A019u);
    y = hfma2(y, m, 0xB82EB82Eu);
    y = hfma2(y, m, 0x3FCF3FCFu);
    const uint32_t w = u + y + 0xC203C204u;
    return and_or(w >> 3, 0x1FFF1FFFu, 0x20002000u);
}

template<int B0, int NB>
__device__ __forceinline__ void softmax_blocks(float (&s)[64], uint32_t (&p)[32]) {
    #pragma unroll
    for (int i = B0 * 4; i < (B0 + NB) * 4; i++) asm volatile("" : "+f"(s[i]) :: "memory");
    #pragma unroll
    for (int b = B0; b < B0 + NB; b++) {
        if ((POLY_BLK >> b) & 1) {
            p[2 * b + 0] = poly_ex2_pair(s[4 * b], s[4 * b + 1]);
            p[2 * b + 1] = poly_ex2_pair(s[4 * b + 2], s[4 * b + 3]);
        } else {
            p[2 * b + 0] = pack_bf16(ex2f(s[4 * b]), ex2f(s[4 * b + 1]));
            p[2 * b + 1] = pack_bf16(ex2f(s[4 * b + 2]), ex2f(s[4 * b + 3]));
        }
    }
}

__device__ __forceinline__ void store_o(int branch, int row0, int h, int t, const float (&o)[12], float r0, float r1) {
    uint32_t* p = (uint32_t*)g_O + ((((branch * 16 + (row0 >> 7)) * 8 + (h >> 2)) * 16 + ((row0 >> 3) & 15)) * 72 + (row0 & 7)) * 4;
    uint32_t* q = p + (h & 3) * 64 + t;
    q[0] = pack_bf16(o[0] * r0, o[1] * r0); q[288] = pack_bf16(o[2] * r1, o[3] * r1);
    q[32] = pack_bf16(o[4] * r0, o[5] * r0); q[288 + 32] = pack_bf16(o[6] * r1, o[7] * r1);
    if (t == 0) { p[256 + (h & 3)] = pack_bf16(o[8] * r0, o[9] * r0); p[288 + 256 + (h & 3)] = pack_bf16(o[10] * r1, o[11] * r1); }
}

#define K2_SMEM (2 * HEAD_BYTES + 24576 + 1536 + 1024)

__global__ void __launch_bounds__(512, 1)
attn_kernel(const __nv_bfloat16* __restrict__ x, const __nv_bfloat16* __restrict__ gate_w,
            const __nv_bfloat16* __restrict__ woA, const __nv_bfloat16* __restrict__ woB) {
    extern __shared__ unsigned char smem_raw[];
    __shared__ __align__(8) uint64_t bars[16];
    const uint32_t sK = (smem_u32(smem_raw) + 1023u) & ~1023u;
    const uint32_t sV = sK + HEAD_BYTES;
    unsigned char* sgen = smem_raw + (sK - smem_u32(smem_raw));
    TSTAMP(1, 0);
    const uint32_t bar0 = smem_u32(bars);
    const int wg = threadIdx.x >> 7, warp = (threadIdx.x >> 5) & 3, lane = threadIdx.x & 31, g = lane >> 2, t = lane & 3;
    if (threadIdx.x == 0) {
        for (int i = 0; i < 16; i++) mbar_init(bar0 + 8 * i, 1);
        asm volatile("fence.mbarrier_init.release.cluster;" ::: "memory");
    }
    __syncthreads();
    pdl_launch();
    const uint32_t kd0 = (sK >> 4) | (8u << 16);
    const uint32_t kd1 = ((sK + 256) >> 4);
    const uint32_t khi = 24;
    const uint32_t vd0 = (sV >> 4) | (24u << 16);
    const uint32_t vhi = 8;

    if (blockIdx.x < 4) {
        const int hb = blockIdx.x * 8 + wg * 2;
        const int tid = threadIdx.x & 127;
        {
            if (threadIdx.x < 8) asm volatile("cp.async.bulk.prefetch.L2.global [%0], %1;" :: "l"((const char*)((blockIdx.x & 1) ? woB : woA) + ((blockIdx.x >> 1) * 8 + threadIdx.x) * 41472), "r"(41472) : "memory");
            uint32_t gv[9];
            #pragma unroll
            for (int i = 0; i < 9; i++) gv[i] = ((const uint32_t*)gate_w)[lane + 32 * i];
            #pragma unroll 1
            for (int r = blockIdx.x * 512 + (threadIdx.x >> 5) * 8; r < blockIdx.x * 512 + 512; r += 128) {
                uint32_t xv[8][9];
                #pragma unroll
                for (int q = 0; q < 8; q++) {
                    #pragma unroll
                    for (int i = 0; i < 9; i++) xv[q][i] = ((const uint32_t*)(x + (size_t)(r + q) * DM))[lane + 32 * i];
                }
                float sum[8];
                #pragma unroll
                for (int q = 0; q < 8; q++) {
                    sum[q] = 0.f;
                    #pragma unroll
                    for (int i = 0; i < 9; i++) sum[q] += bfr(bf_lo(xv[q][i]) * bf_lo(gv[i])) + bfr(bf_hi(xv[q][i]) * bf_hi(gv[i]));
                }
                #pragma unroll
                for (int o = 16; o > 0; o >>= 1) {
                    #pragma unroll
                    for (int q = 0; q < 8; q++) sum[q] += __shfl_xor_sync(~0u, sum[q], o);
                }
                float z = sum[0];
                #pragma unroll
                for (int q = 1; q < 8; q++) z = lane == q ? sum[q] : z;
                if (lane < 8) g_gate[r + lane] = bfr(1.0f / (1.0f + __expf(-bfr(z))));
            }
        }
        TSTAMP(1, 3);
        pdl_wait();
        TSTAMP(1, 1);
        const uint32_t slot0 = sK + wg * 49152, fb0 = bar0 + wg * 16;
        auto issue = [&](int c) {
            mbar_expect_tx(fb0 + 8 * (c & 1), 24576);
            bulk_g2s(slot0 + (c & 1) * 24576, (const char*)(g_T + (size_t)(NH + 2 * hb) * HEAD_ELEMS) + (size_t)c * 24576, 24576, fb0 + 8 * (c & 1));
        };
        if (tid == 0) { issue(0); issue(1); }
        #pragma unroll 1
        for (int hi = 0; hi < 2; hi++) {
            float d1[4][12];
            #pragma unroll
            for (int k = 0; k < 4; k++) {
                #pragma unroll
                for (int i = 0; i < 12; i++) d1[k][i] = 0.f;
                fence_regs(d1[k]);
            }
            #pragma unroll 1
            for (int cc = 0; cc < 8; cc++) {
                const int c = hi * 8 + cc;
                mbar_wait_w(fb0 + 8 * (c & 1), (c >> 1) & 1);
                const uint32_t base = ((slot0 + (c & 1) * 24576) >> 4) | (24u << 16);
                WG_FENCE();
                #pragma unroll
                for (int ks = 0; ks < 16; ks++)
                    wgmma_n24_ss<1, 1>(d1[ks & 3], mkdesc(base + ks * 48, 8u), mkdesc(base + 768 + ks * 48, vhi), 1);
                WG_COMMIT();
                WG_WAIT(0);
                named_bar(1 + wg, 128);
                if (tid == 0 && c + 2 < 16) issue(c + 2);
            }
            #pragma unroll
            for (int k = 0; k < 4; k++) fence_regs(d1[k]);
            #pragma unroll
            for (int i = 0; i < 12; i++) d1[0][i] = (d1[0][i] + d1[1][i]) + (d1[2][i] + d1[3][i]);
            if (warp < 2) {
                const int d = warp * 16 + g;
                uint32_t* kp = (uint32_t*)(g_kv + (hb + hi) * 768 + (d >> 3) * 192 + (d & 7) * 8 + 2 * t);
                #pragma unroll
                for (int j = 0; j < 3; j++) {
                    kp[32 * j] = d < 18 ? pack_bf16(d1[0][4 * j], d1[0][4 * j + 1]) : 0u;
                    kp[96 + 32 * j] = warp == 0 ? pack_bf16(d1[0][4 * j + 2], d1[0][4 * j + 3]) : 0u;
                }
                __threadfence();
            }
            named_bar(1 + wg, 128);
            if (tid == 0) asm volatile("st.release.gpu.global.b32 [%0], %1;" :: "l"(g_kvflag + hb + hi), "r"(1) : "memory");
        }
        TSTAMP(1, 4);
        TSTAMP(1, 2);
        return;
    }
    const int cta = blockIdx.x - 4;

#define WT_CTAS 128
    if (cta < WT_CTAS) {
        constexpr int PER = 82944 / WT_CTAS, NQ = (PER + 511) / 512;
        uint4 wv[NQ];
        #pragma unroll
        for (int q = 0; q < NQ; q++) {
            const int id = cta * PER + threadIdx.x + q * 512;
            if (threadIdx.x + q * 512 < PER) wv[q] = *(const uint4*)((id >= 41472 ? woB - 41472 * 8 : woA) + (size_t)id * 8);
        }
        #pragma unroll
        for (int q = 0; q < NQ; q++) {
            const int id = cta * PER + threadIdx.x + q * 512;
            const int b = id >= 41472, r2 = id - b * 41472, k = r2 / 72, c = r2 % 72;
            const int hh = k / 18, d = k % 18;
            const int kp = (hh >> 2) * 72 + (d < 16 ? (hh & 3) * 16 + d : 64 + (hh & 3) * 2 + (d - 16));
            if (threadIdx.x + q * 512 < PER) *(uint4*)(g_Wt + ((((c / 24) * 2 + b) * 8 + kp / 72) * 24 + (c % 24)) * 576 + (kp % 72) * 8) = wv[q];
        }
    }

    const int h = cta >> 2, quarter = cta & 3;
    const uint32_t sPQ = sK + 2 * HEAD_BYTES, sKVt = sPQ + 24576;
    pdl_wait();
    TSTAMP(1, 1);
    auto issue_kv = [&](int c) {
        mbar_expect_tx(bar0 + 8 * c, 24576);
        bulk_g2s(sK + c * 12288, (const char*)(g_T + (size_t)(4 * NH + h) * HEAD_ELEMS) + c * 12288, 12288, bar0 + 8 * c);
        bulk_g2s(sV + c * 12288, (const char*)(g_T + (size_t)(5 * NH + h) * HEAD_ELEMS) + c * 12288, 12288, bar0 + 8 * c);
    };
    int kv_state = 0;
    auto kv_poll = [&](bool block) {
        if (threadIdx.x == 0 && kv_state != 2) {
            while (block && kv_state == 0) asm volatile("ld.acquire.gpu.global.b32 %0, [%1];" : "=r"(kv_state) : "l"(g_kvflag + h) : "memory");
            if (kv_state == 1) {
                asm volatile("fence.proxy.async.global;" ::: "memory");
                mbar_expect_tx(bar0 + 72, 1536);
                bulk_g2s(sKVt, g_kv + h * 768, 1536, bar0 + 72);
                kv_state = 2;
            } else {
                asm volatile("ld.acquire.gpu.global.b32 %0, [%1];" : "=r"(kv_state) : "l"(g_kvflag + h) : "memory");
            }
        }
    };
    float km2 = 0.f;
    #pragma unroll
    for (int i = 0; i < 8; i++) km2 = fmaxf(km2, g_kmax[i][h]);
    int s_fast_tmp = 0;
    uint32_t zr = 0u;
    asm volatile("" : "+r"(zr));
    uint32_t qf[2][6];
    #pragma unroll
    for (int pass = 0; pass < 2; pass++) {
        const int row0 = quarter * 512 + (wg * 2 + pass) * 64 + warp * 16 + g;
        const uint32_t* q0 = (const uint32_t*)(g_T + (size_t)(3 * NH + h) * HEAD_ELEMS + (row0 >> 3) * 192 + (row0 & 7) * 8) + t;
        qf[pass][0] = q0[0]; qf[pass][1] = q0[96]; qf[pass][2] = q0[32]; qf[pass][3] = q0[128];
        qf[pass][4] = q0[64]; qf[pass][5] = q0[160];
    }
    if (threadIdx.x == 0) issue_kv(0);
    if (threadIdx.x == 128) issue_kv(1);
    __syncwarp();
    #pragma unroll
    for (int i = 0; i < 6; i++) { qf[0][i] = qscale_pair(qf[0][i]); qf[1][i] = qscale_pair(qf[1][i]); }
    float mrow[2][2];
    bool ok = true;
    #pragma unroll
    for (int pass = 0; pass < 2; pass++) {
        auto sq = [](uint32_t v) { float a = bf_lo(v), b = bf_hi(v); return a * a + b * b; };
        float n0 = sq(qf[pass][0]) + sq(qf[pass][2]) + sq(qf[pass][4]);
        float n1 = sq(qf[pass][1]) + sq(qf[pass][3]) + sq(qf[pass][5]);
        n0 += __shfl_xor_sync(~0u, n0, 1); n0 += __shfl_xor_sync(~0u, n0, 2);
        n1 += __shfl_xor_sync(~0u, n1, 1); n1 += __shfl_xor_sync(~0u, n1, 2);
        mrow[pass][0] = sqrtf(n0 * km2) * 1.01f + 0.01f;
        mrow[pass][1] = sqrtf(n1 * km2) * 1.01f + 0.01f;
        ok = ok && (mrow[pass][0] <= 31.0f) && (mrow[pass][1] <= 31.0f);
    }
    bool fast;
    asm volatile("{\n.reg .pred p, q;\nsetp.ne.b32 p, %1, 0;\nbar.red.and.pred q, %2, 128, p;\nselp.b32 %0, 1, 0, q;\n}\n"
                 : "=r"(*(int*)&s_fast_tmp) : "r"((int)ok), "r"(1 + wg) : "memory");
    fast = __all_sync(0xFFFFFFFFu, s_fast_tmp != 0);
    TSTAMP(1, 3);

    #pragma unroll 1
    for (int pass = 0; pass < 2; pass++) {
        const int row0 = quarter * 512 + (wg * 2 + pass) * 64 + warp * 16 + g;
        uint32_t qa[6];
        #pragma unroll
        for (int i = 0; i < 6; i++) qa[i] = pass ? qf[1][i] : qf[0][i];
        float o[12];
        #pragma unroll
        for (int i = 0; i < 12; i++) o[i] = 0.f;
        fence_regs(o);
        float s[64]; uint32_t p[32];
        #pragma unroll
        for (int i = 0; i < 64; i++) s[i] = 0.f;
        fence_regs(s);
        if (fast) {
            if (t == 1) { qa[4] = pack_bf16(-(pass ? mrow[1][0] : mrow[0][0]), 1.0f); qa[5] = pack_bf16(-(pass ? mrow[1][1] : mrow[0][1]), 1.0f); }
            #pragma unroll 1
            for (int j = 0; j < 16; j++) {
                if (pass == 0 && (j & 1) == 0) {
                    const int cn = (j >> 1) + 2;
                    if ((threadIdx.x & 127) == 0 && (cn & 3) == wg) {
                        if (cn < 8) issue_kv(cn);
                        else if (cn == 8) { mbar_expect_tx(bar0 + 64, 24576); bulk_g2s(sPQ, (const char*)(g_T + (size_t)h * HEAD_ELEMS) + quarter * 24576, 24576, bar0 + 64); }
                    }
                    mbar_wait_w(bar0 + 8 * (j >> 1), 0);
                }
                const uint32_t ko = j * 384;
                WG_FENCE();
                wgmma_n128_rs<0>(s, qa[0], qa[1], qa[2], qa[3], mkdesc(kd0 + ko, khi));
                wgmma_n128_rs<1>(s, qa[4], qa[5], zr, zr, mkdesc(kd1 + ko, khi));
                WG_COMMIT();
                if (pass == 1 && (j & 3) == 3) { kv_poll(false); __syncwarp(); }
                WG_WAIT(0);
                #pragma unroll
                for (int qd = 0; qd < 4; qd++) {
                    if (qd == 0) softmax_blocks<0, 4>(s, p);
                    if (qd == 1) softmax_blocks<4, 4>(s, p);
                    if (qd == 2) softmax_blocks<8, 4>(s, p);
                    if (qd == 3) softmax_blocks<12, 4>(s, p);
                    WG_FENCE();
                    wgmma_n24_rs(o, p[qd * 8 + 0], p[qd * 8 + 1], p[qd * 8 + 2], p[qd * 8 + 3], mkdesc(vd0 + ko + qd * 96, vhi));
                    wgmma_n24_rs(o, p[qd * 8 + 4], p[qd * 8 + 5], p[qd * 8 + 6], p[qd * 8 + 7], mkdesc(vd0 + ko + qd * 96 + 48, vhi));
                    WG_COMMIT();
                }
                WG_WAIT(0);
            }
        } else {
            {
                const uint32_t* q0 = (const uint32_t*)(g_T + (size_t)(3 * NH + h) * HEAD_ELEMS + (row0 >> 3) * 192 + (row0 & 7) * 8) + t;
                qa[0] = q0[0]; qa[1] = q0[96]; qa[2] = q0[32]; qa[3] = q0[128]; qa[4] = q0[64]; qa[5] = q0[160];
            }
            const float qs = 0.23570226039551584f * 1.4426950408889634f;
            float mr0 = -INFINITY, mr1 = -INFINITY;
            #pragma unroll 1
            for (int j = 0; j < 16; j++) {
                if (pass == 0 && (j & 1) == 0) {
                    const int cn = (j >> 1) + 2;
                    if ((threadIdx.x & 127) == 0 && (cn & 3) == wg) {
                        if (cn < 8) issue_kv(cn);
                        else if (cn == 8) { mbar_expect_tx(bar0 + 64, 24576); bulk_g2s(sPQ, (const char*)(g_T + (size_t)h * HEAD_ELEMS) + quarter * 24576, 24576, bar0 + 64); }
                    }
                    mbar_wait_w(bar0 + 8 * (j >> 1), 0);
                }
                const uint32_t ko = j * 384;
                WG_FENCE();
                wgmma_n128_rs<0>(s, qa[0], qa[1], qa[2], qa[3], mkdesc(kd0 + ko, khi));
                wgmma_n128_rs<1>(s, qa[4], qa[5], zr, zr, mkdesc(kd1 + ko, khi));
                WG_COMMIT();
                WG_WAIT(0);
                fence_regs(s); fence_regs(o);
                float x0 = mr0, x1 = mr1;
                #pragma unroll
                for (int b = 0; b < 16; b++) {
                    x0 = fmaxf(x0, fmaxf(s[4 * b], s[4 * b + 1]));
                    x1 = fmaxf(x1, fmaxf(s[4 * b + 2], s[4 * b + 3]));
                }
                x0 = fmaxf(x0, __shfl_xor_sync(~0u, x0, 1)); x0 = fmaxf(x0, __shfl_xor_sync(~0u, x0, 2));
                x1 = fmaxf(x1, __shfl_xor_sync(~0u, x1, 1)); x1 = fmaxf(x1, __shfl_xor_sync(~0u, x1, 2));
                const float c0 = exp2f((mr0 - x0) * qs), c1 = exp2f((mr1 - x1) * qs);
                mr0 = x0; mr1 = x1;
                #pragma unroll
                for (int i = 0; i < 12; i++) o[i] *= (i & 2) ? c1 : c0;
                #pragma unroll
                for (int b = 0; b < 16; b++) {
                    p[2 * b] = pack_bf16(exp2f((s[4 * b] - x0) * qs), exp2f((s[4 * b + 1] - x0) * qs));
                    p[2 * b + 1] = pack_bf16(exp2f((s[4 * b + 2] - x1) * qs), exp2f((s[4 * b + 3] - x1) * qs));
                }
                fence_regs(o);
                WG_FENCE();
                #pragma unroll
                for (int kk = 0; kk < 8; kk++)
                    wgmma_n24_rs(o, p[kk * 4 + 0], p[kk * 4 + 1], p[kk * 4 + 2], p[kk * 4 + 3], mkdesc(vd0 + ko + kk * 48, vhi));
                WG_COMMIT();
                WG_WAIT(0);
            }
        }
        fence_regs(o);
        const float l0 = __shfl_sync(~0u, o[8], (lane & ~3) | 1);
        const float l1 = __shfl_sync(~0u, o[10], (lane & ~3) | 1);
        store_o(1, row0, h, t, o, 1.0f / l0, 1.0f / l1);
    }
    TSTAMP(1, 4);
    {
        kv_poll(true); kv_poll(true);
        mbar_wait_w(bar0 + 64, 0);
        phi_inplace<3>(sgen + 2 * HEAD_BYTES + wg * 6144, threadIdx.x & 127);
        named_bar(1 + wg, 128);
        mbar_wait_w(bar0 + 72, 0);
        float e[4][12];
        #pragma unroll
        for (int k = 0; k < 4; k++) {
            #pragma unroll
            for (int i = 0; i < 12; i++) e[k][i] = 0.f;
            fence_regs(e[k]);
        }
        const uint32_t ab = (sPQ + wg * 6144) >> 4, bb = (sKVt >> 4) | (24u << 16);
        WG_FENCE();
        wgmma_n24_ss<0, 1>(e[0], mkdesc(ab | (8u << 16), khi), mkdesc(bb, vhi), 0);
        wgmma_n24_ss<0, 1>(e[1], mkdesc((ab + 192) | (8u << 16), khi), mkdesc(bb, vhi), 0);
        wgmma_n24_ss<0, 1>(e[2], mkdesc(ab + 16, khi), mkdesc(bb + 48, vhi), 0);
        wgmma_n24_ss<0, 1>(e[3], mkdesc(ab + 192 + 16, khi), mkdesc(bb + 48, vhi), 0);
        WG_COMMIT();
        WG_WAIT(0);
        #pragma unroll
        for (int k = 0; k < 4; k++) fence_regs(e[k]);
        #pragma unroll
        for (int m = 0; m < 2; m++) {
            #pragma unroll
            for (int i = 0; i < 12; i++) e[m][i] = bfr(e[m][i] + e[m + 2][i]);
            const float l0 = __shfl_sync(~0u, e[m][8], (lane & ~3) | 1), l1 = __shfl_sync(~0u, e[m][10], (lane & ~3) | 1);
            store_o(0, quarter * 512 + (wg * 2 + m) * 64 + warp * 16 + g, h, t, e[m], 1.0f / bfr(l0 + 1e-6f), 1.0f / bfr(l1 + 1e-6f));
        }
    }
    TSTAMP(1, 2);
}

#define K3_UNITS 4
#define K3_UNIT_BYTES 46080
#define K3_SMEM (K3_UNITS * K3_UNIT_BYTES + 26624 + 1024)

__global__ void __cluster_dims__(2, 1, 1) __launch_bounds__(288, 1)
out_kernel(__nv_bfloat16* __restrict__ out) {
    extern __shared__ unsigned char smem_raw[];
    __shared__ __align__(8) uint64_t bars[2 * K3_UNITS + 8];
    const uint32_t sA = (smem_u32(smem_raw) + 1023u) & ~1023u;
    const uint32_t sX = sA + K3_UNITS * K3_UNIT_BYTES;
    const uint32_t full0 = smem_u32(bars), empty0 = full0 + 8 * K3_UNITS;
    const int br = blockIdx.x & 1, tile = blockIdx.x >> 1, mt = tile / 3, nt = tile % 3;
    const int m0 = mt * 128, n0 = nt * 192;
    TSTAMP(2, 0);
    if (threadIdx.x == 0) {
        for (int i = 0; i < K3_UNITS; i++) { mbar_init(full0 + 8 * i, 1); mbar_init(empty0 + 8 * i, 2); }
        for (int i = 0; i < 8; i++) mbar_init(full0 + 16 * K3_UNITS + 8 * i, 1);
        asm volatile("fence.mbarrier_init.release.cluster;" ::: "memory");
    }
    __syncthreads();
    cluster_arrive();
    TSTAMP(2, 3);
    pdl_wait();
    TSTAMP(2, 1);
    const int wg = threadIdx.x >> 7;
    if (wg == 2) {
        if (threadIdx.x == 256) {
            for (int c = 0; c < 8; c++) {
                const int s = c % K3_UNITS;
                if (c >= K3_UNITS) mbar_wait(empty0 + 8 * s, 0);
                const uint32_t st = sA + s * K3_UNIT_BYTES;
                mbar_expect_tx(full0 + 8 * s, K3_UNIT_BYTES);
                bulk_g2s(st, g_O + (size_t)((br * 16 + mt) * 8 + c) * 9216, 18432, full0 + 8 * s);
                bulk_g2s(st + 18432, g_Wt + (size_t)((nt * 2 + br) * 8 + c) * 13824, 27648, full0 + 8 * s);
            }
        }
        __syncwarp();
        cluster_wait();
        cluster_arrive();
    } else {
        const int warp = (threadIdx.x >> 5) & 3, lane = threadIdx.x & 31, g = lane >> 2, t = lane & 3;
        float acc[96];
        #pragma unroll
        for (int i = 0; i < 96; i++) acc[i] = 0.f;
        fence_regs(acc);
        const uint32_t hiA = 72u;
        const uint32_t hiB = 72u;
        const int r0 = m0 + wg * 64 + warp * 16 + g;
        float g0 = g_gate[r0], g1 = g_gate[r0 + 8];
        if (br) { g0 = bfr(1.0f - g0); g1 = bfr(1.0f - g1); }
        #pragma unroll 1
        for (int pr = 0; pr < 4; pr++) {
            const int s = (pr & 1) * 2;
            const uint32_t a_lo = ((sA + s * K3_UNIT_BYTES + wg * 9216) & 0x3FFFF) >> 4;
            const uint32_t b_lo = ((sA + s * K3_UNIT_BYTES + 18432) & 0x3FFFF) >> 4;
            mbar_wait_w(full0 + 8 * s, pr >> 1);
            if (pr == 0) TSTAMP(2, 4);
            WG_FENCE();
            #pragma unroll
            for (int i = 0; i < 4; i++) wgmma_n192_ss(acc, mkdesc((a_lo + i * 16) | (8u << 16), hiA), mkdesc((b_lo + i * 16) | (8u << 16), hiB), 1);
            WG_COMMIT();
            mbar_wait_w(full0 + 8 * s + 8, pr >> 1);
            WG_FENCE();
            wgmma_n192_ss(acc, mkdesc((a_lo + 64) | ((K3_UNIT_BYTES / 16 - 64) << 16), hiA), mkdesc((b_lo + 64) | ((K3_UNIT_BYTES / 16 - 64) << 16), hiB), 1);
            #pragma unroll
            for (int i = 0; i < 4; i++)
                wgmma_n192_ss(acc, mkdesc((a_lo + K3_UNIT_BYTES / 16 + 8 + i * 16) | (8u << 16), hiA), mkdesc((b_lo + K3_UNIT_BYTES / 16 + 8 + i * 16) | (8u << 16), hiB), 1);
            WG_COMMIT();
            if (pr < 2) {
                WG_WAIT(0);
                if ((threadIdx.x & 127) < 2) mbar_arrive(empty0 + 8 * (s + (threadIdx.x & 1)));
            }
        }
        WG_WAIT(0);
        fence_regs(acc);
        TSTAMP(2, 5);
        uint32_t keep[24];
        named_bar(1, 256);
        const uint32_t snd = sA + (wg * 4 + warp) * 3328;
        #pragma unroll
        for (int j = 0; j < 24; j++) {
            const uint32_t v0 = pack_bf16(g0 * bfr(acc[4 * j]), g0 * bfr(acc[4 * j + 1]));
            const uint32_t v1 = pack_bf16(g1 * bfr(acc[4 * j + 2]), g1 * bfr(acc[4 * j + 3]));
            const int jj = j % 12;
            if ((j < 12) == (br == 0)) { keep[2 * jj] = v0; keep[2 * jj + 1] = v1; }
            else { sts32(snd + g * 208 + jj * 16 + t * 4, v0); sts32(snd + (g + 8) * 208 + jj * 16 + t * 4, v1); }
        }
        fence_async();
        __syncwarp();
        cluster_wait();
        const uint32_t xbar = full0 + 16 * K3_UNITS + 8 * (wg * 4 + warp);
        if (lane == 0) {
            uint32_t rdst, rbar;
            asm volatile("mapa.shared::cluster.u32 %0, %1, %2;" : "=r"(rdst) : "r"(sX + (wg * 4 + warp) * 3328), "r"(br ^ 1));
            asm volatile("mapa.shared::cluster.u32 %0, %1, %2;" : "=r"(rbar) : "r"(xbar), "r"(br ^ 1));
            mbar_expect_tx(xbar, 3328);
            asm volatile("cp.async.bulk.shared::cluster.shared::cta.mbarrier::complete_tx::bytes [%0], [%1], %2, [%3];"
                         :: "r"(rdst), "r"(snd), "r"(3328), "r"(rbar) : "memory");
        }
        mbar_wait_w(xbar, 0);
        cluster_arrive();
        const uint32_t sx = sX + (wg * 64 + warp * 16) * 208;
        #pragma unroll
        for (int jj = 0; jj < 12; jj++) {
            uint32_t p0, p1;
            asm volatile("ld.shared.b32 %0, [%1];" : "=r"(p0) : "r"(sx + g * 208 + jj * 16 + t * 4));
            asm volatile("ld.shared.b32 %0, [%1];" : "=r"(p1) : "r"(sx + (g + 8) * 208 + jj * 16 + t * 4));
            sts32(sx + g * 208 + jj * 16 + t * 4, hadd2_bf16(keep[2 * jj], p0));
            sts32(sx + (g + 8) * 208 + jj * 16 + t * 4, hadd2_bf16(keep[2 * jj + 1], p1));
        }
        __syncwarp();
        #pragma unroll
        for (int i = 0; i < 6; i++) {
            const int id = i * 32 + lane, r = id / 12, c = id % 12;
            uint4 v;
            asm volatile("ld.shared.v4.b32 {%0,%1,%2,%3}, [%4];" : "=r"(v.x), "=r"(v.y), "=r"(v.z), "=r"(v.w) : "r"(sx + r * 208 + c * 16));
            *(uint4*)(out + (size_t)(m0 + wg * 64 + warp * 16 + r) * DM + n0 + br * 96 + c * 8) = v;
        }
        TSTAMP(2, 2);
    }
    cluster_wait();
}

typedef CUresult (*EncodeFn)(CUtensorMap*, CUtensorMapDataType, cuuint32_t, void*, const cuuint64_t*, const cuuint64_t*,
                             const cuuint32_t*, const cuuint32_t*, CUtensorMapInterleave, CUtensorMapSwizzle,
                             CUtensorMapL2promotion, CUtensorMapFloatOOBfill);

static void make_map(EncodeFn enc, CUtensorMap* m, const void* base, uint64_t inner, uint64_t outer, uint32_t box_in, uint32_t box_out, CUtensorMapSwizzle sw) {
    cuuint64_t dims[2] = {inner, outer};
    cuuint64_t strides[1] = {inner * 2};
    cuuint32_t box[2] = {box_in, box_out};
    cuuint32_t es[2] = {1, 1};
    enc(m, CU_TENSOR_MAP_DATA_TYPE_BFLOAT16, 2, (void*)base, dims, strides, box, es, CU_TENSOR_MAP_INTERLEAVE_NONE, sw,
        CU_TENSOR_MAP_L2_PROMOTION_L2_256B, CU_TENSOR_MAP_FLOAT_OOB_FILL_NONE);
}

extern "C" void kernel_launch(void* const* d_in, const int* in_sizes, int n_in, void* d_out, int out_size) {
    const __nv_bfloat16* x = (const __nv_bfloat16*)d_in[0];
    const __nv_bfloat16* wA = (const __nv_bfloat16*)d_in[1];
    const __nv_bfloat16* woA = (const __nv_bfloat16*)d_in[2];
    const __nv_bfloat16* wB = (const __nv_bfloat16*)d_in[4];
    const __nv_bfloat16* woB = (const __nv_bfloat16*)d_in[5];
    const __nv_bfloat16* gw = (const __nv_bfloat16*)d_in[6];
    __nv_bfloat16* out = (__nv_bfloat16*)d_out;

    static EncodeFn enc = nullptr;
    if (!enc) {
        void* fn = nullptr; cudaDriverEntryPointQueryResult st;
        cudaGetDriverEntryPoint("cuTensorMapEncodeTiled", &fn, cudaEnableDefault, &st);
        enc = (EncodeFn)fn;
        cudaFuncSetAttribute(qkv_kernel, cudaFuncAttributeMaxDynamicSharedMemorySize, K1_SMEM);
        cudaFuncSetAttribute(attn_kernel, cudaFuncAttributeMaxDynamicSharedMemorySize, K2_SMEM);
        cudaFuncSetAttribute(out_kernel, cudaFuncAttributeMaxDynamicSharedMemorySize, K3_SMEM);
    }
    CUtensorMap mX, mWA, mWA2, mWB, mWB2;
    make_map(enc, &mX, x, DM, S_LEN, 64, 256, CU_TENSOR_MAP_SWIZZLE_128B);
    make_map(enc, &mWA, wA, 3 * DM, DM, 64, 64, CU_TENSOR_MAP_SWIZZLE_128B);
    make_map(enc, &mWA2, wA, 3 * DM, DM, 32, 64, CU_TENSOR_MAP_SWIZZLE_64B);
    make_map(enc, &mWB, wB, 3 * DM, DM, 64, 64, CU_TENSOR_MAP_SWIZZLE_128B);
    make_map(enc, &mWB2, wB, 3 * DM, DM, 32, 64, CU_TENSOR_MAP_SWIZZLE_64B);

    cudaStream_t stream = cudaStreamPerThread;
    cudaLaunchAttribute at[1];
    at[0].id = cudaLaunchAttributeProgrammaticStreamSerialization;
    at[0].val.programmaticStreamSerializationAllowed = 1;

    qkv_kernel<<<128, 256, K1_SMEM, stream>>>(mX, mWA, mWA2, mWB, mWB2);

    cudaLaunchConfig_t c2 = {};
    c2.gridDim = dim3(132); c2.blockDim = dim3(512); c2.dynamicSmemBytes = K2_SMEM; c2.stream = stream; c2.attrs = at; c2.numAttrs = 1;
    cudaLaunchKernelEx(&c2, attn_kernel, x, gw, woA, woB);

    cudaLaunchConfig_t c3 = {};
    c3.gridDim = dim3(96); c3.blockDim = dim3(288); c3.dynamicSmemBytes = K3_SMEM; c3.stream = stream; c3.attrs = at; c3.numAttrs = 1;
    cudaLaunchKernelEx(&c3, out_kernel, out);
}
```

```cpp
#include <cuda_runtime.h>
#include <cuda_bf16.h>
#include <cuda.h>
#include <stdint.h>

#define S_LEN 2048
#define DM 576
#define NH 32
#define DH 18
#define HEAD_ELEMS 49152
#define HEAD_BYTES 98304

#define POLY_BLK 0xAAAA

__device__ __align__(1024) __nv_bfloat16 g_T[6 * NH * HEAD_ELEMS];
__device__ float g_kmax[8][NH];
__device__ __align__(1024) __nv_bfloat16 g_O[2 * S_LEN * DM];
__device__ float g_gate[S_LEN];
__device__ __align__(128) __nv_bfloat16 g_kv[NH * 768];
__device__ int g_kvflag[NH];
__device__ __align__(1024) __nv_bfloat16 g_Wt[3 * 2 * 8 * 13824];

#define TSTAMP(k, i)
#define WG_FENCE() asm volatile("wgmma.fence.sync.aligned;\n" ::: "memory")
#define WG_COMMIT() asm volatile("wgmma.commit_group.sync.aligned;\n" ::: "memory")
#define WG_WAIT(n) asm volatile("wgmma.wait_group.sync.aligned %0;\n" :: "n"(n) : "memory")

__device__ __forceinline__ uint64_t mkdesc(uint32_t lo, uint32_t hi) {
    uint64_t d; asm("mov.b64 %0, {%1, %2};" : "=l"(d) : "r"(lo), "r"(hi)); return d;
}
__device__ __forceinline__ uint32_t smem_u32(const void* p) { return (uint32_t)__cvta_generic_to_shared(p); }
__device__ __forceinline__ void mbar_init(uint32_t bar, uint32_t cnt) { asm volatile("mbarrier.init.shared::cta.b64 [%0], %1;" :: "r"(bar), "r"(cnt)); }
__device__ __forceinline__ void mbar_expect_tx(uint32_t bar, uint32_t bytes) { asm volatile("mbarrier.arrive.expect_tx.shared::cta.b64 _, [%0], %1;" :: "r"(bar), "r"(bytes) : "memory"); }
__device__ __forceinline__ void mbar_arrive(uint32_t bar) { asm volatile("mbarrier.arrive.shared::cta.b64 _, [%0];" :: "r"(bar) : "memory"); }
__device__ __forceinline__ void mbar_wait(uint32_t bar, uint32_t parity) {
    asm volatile("{\n.reg .pred p;\nWAIT_%=:\nmbarrier.try_wait.parity.shared::cta.b64 p, [%0], %1;\n@p bra DONE_%=;\nbra WAIT_%=;\nDONE_%=:\n}\n" :: "r"(bar), "r"(parity) : "memory");
}
__device__ __forceinline__ void mbar_wait_w(uint32_t bar, uint32_t parity) { __syncwarp(); mbar_wait(bar, parity); }
__device__ __forceinline__ void bulk_g2s(uint32_t dst, const void* src, uint32_t bytes, uint32_t bar) {
    asm volatile("cp.async.bulk.shared::cluster.global.mbarrier::complete_tx::bytes [%0], [%1], %2, [%3];" :: "r"(dst), "l"(src), "r"(bytes), "r"(bar) : "memory");
}
__device__ __forceinline__ void tma_2d(uint32_t dst, const CUtensorMap* map, int c0, int c1, uint32_t bar) {
    asm volatile("cp.async.bulk.tensor.2d.shared::cluster.global.mbarrier::complete_tx::bytes [%0], [%1, {%3, %4}], [%2];"
                 :: "r"(dst), "l"((uint64_t)map), "r"(bar), "r"(c0), "r"(c1) : "memory");
}
__device__ __forceinline__ void cluster_arrive() { asm volatile("barrier.cluster.arrive.release.aligned;" ::: "memory"); }
__device__ __forceinline__ void cluster_wait() { asm volatile("barrier.cluster.wait.acquire.aligned;" ::: "memory"); }
__device__ __forceinline__ void named_bar(int id, int n) { asm volatile("bar.sync %0, %1;" :: "r"(id), "r"(n) : "memory"); }
__device__ __forceinline__ void fence_async() { asm volatile("fence.proxy.async.shared::cta;" ::: "memory"); }
__device__ __forceinline__ void pdl_wait() { asm volatile("griddepcontrol.wait;" ::: "memory"); }
__device__ __forceinline__ void pdl_launch() { asm volatile("griddepcontrol.launch_dependents;" ::: "memory"); }

__device__ __forceinline__ float ex2f(float x) { float y; asm("ex2.approx.ftz.f32 %0, %1;" : "=f"(y) : "f"(x)); return y; }
__device__ __forceinline__ uint32_t pack_bf16(float lo, float hi) { uint32_t r; asm("cvt.rn.bf16x2.f32 %0, %1, %2;" : "=r"(r) : "f"(hi), "f"(lo)); return r; }
__device__ __forceinline__ float bf_lo(uint32_t v) { return __uint_as_float(v << 16); }
__device__ __forceinline__ float bf_hi(uint32_t v) { return __uint_as_float(v & 0xFFFF0000u); }
__device__ __forceinline__ float bfr(float x) { return __uint_as_float(pack_bf16(0.f, x) & 0xFFFF0000u); }

#define ACC4(a, o) "+f"(a[o]), "+f"(a[o + 1]), "+f"(a[o + 2]), "+f"(a[o + 3])
#define ACC12(a, o) ACC4(a, o), ACC4(a, o + 4), ACC4(a, o + 8)
#define ACC16(a, o) ACC4(a, o), ACC4(a, o + 4), ACC4(a, o + 8), ACC4(a, o + 12)
#define ACC32(a, o) ACC16(a, o), ACC16(a, o + 16)

__device__ __forceinline__ void wgmma_n24_rs(float (&d)[12], uint32_t a0, uint32_t a1, uint32_t a2, uint32_t a3, uint64_t bdesc) {
    asm volatile("{\n.reg .pred p;\nsetp.ne.b32 p, 1, 0;\n"
        "wgmma.mma_async.sync.aligned.m64n24k16.f32.bf16.bf16 "
        "{%0,%1,%2,%3,%4,%5,%6,%7,%8,%9,%10,%11}, {%12,%13,%14,%15}, %16, p, 1, 1, 1;\n}\n"
        : ACC12(d, 0) : "r"(a0), "r"(a1), "r"(a2), "r"(a3), "l"(bdesc));
}
template<int TA, int TB>
__device__ __forceinline__ void wgmma_n24_ss(float (&d)[12], uint64_t adesc, uint64_t bdesc, int acc) {
    asm volatile("{\n.reg .pred p;\nsetp.ne.b32 p, %14, 0;\n"
        "wgmma.mma_async.sync.aligned.m64n24k16.f32.bf16.bf16 "
        "{%0,%1,%2,%3,%4,%5,%6,%7,%8,%9,%10,%11}, %12, %13, p, 1, 1, %15, %16;\n}\n"
        : ACC12(d, 0) : "l"(adesc), "l"(bdesc), "r"(acc), "n"(TA), "n"(TB));
}
template<int ACC>
__device__ __forceinline__ void wgmma_n128_rs(float (&d)[64], uint32_t a0, uint32_t a1, uint32_t a2, uint32_t a3, uint64_t bdesc) {
    asm volatile("{\n.reg .pred p;\nsetp.ne.b32 p, %69, 0;\n"
        "wgmma.mma_async.sync.aligned.m64n128k16.f32.bf16.bf16 "
        "{%0,%1,%2,%3,%4,%5,%6,%7,%8,%9,%10,%11,%12,%13,%14,%15,%16,%17,%18,%19,%20,%21,%22,%23,%24,%25,%26,%27,%28,%29,%30,%31,"
        "%32,%33,%34,%35,%36,%37,%38,%39,%40,%41,%42,%43,%44,%45,%46,%47,%48,%49,%50,%51,%52,%53,%54,%55,%56,%57,%58,%59,%60,%61,%62,%63}, {%64,%65,%66,%67}, %68, p, 1, 1, 0;\n}\n"
        : ACC32(d, 0), ACC32(d, 32) : "r"(a0), "r"(a1), "r"(a2), "r"(a3), "l"(bdesc), "n"(ACC));
}
__device__ __forceinline__ void wgmma_n192_ss(float (&d)[96], uint64_t adesc, uint64_t bdesc, int acc) {
    asm volatile("{\n.reg .pred p;\nsetp.ne.b32 p, %98, 0;\n"
        "wgmma.mma_async.sync.aligned.m64n192k16.f32.bf16.bf16 "
        "{%0,%1,%2,%3,%4,%5,%6,%7,%8,%9,%10,%11,%12,%13,%14,%15,%16,%17,%18,%19,%20,%21,%22,%23,%24,%25,%26,%27,%28,%29,%30,%31,"
        "%32,%33,%34,%35,%36,%37,%38,%39,%40,%41,%42,%43,%44,%45,%46,%47,%48,%49,%50,%51,%52,%53,%54,%55,%56,%57,%58,%59,%60,%61,%62,%63,"
        "%64,%65,%66,%67,%68,%69,%70,%71,%72,%73,%74,%75,%76,%77,%78,%79,%80,%81,%82,%83,%84,%85,%86,%87,%88,%89,%90,%91,%92,%93,%94,%95}, %96, %97, p, 1, 1, 0, 1;\n}\n"
        : ACC32(d, 0), ACC32(d, 32), ACC32(d, 64) : "l"(adesc), "l"(bdesc), "r"(acc));
}
template<int N> __device__ __forceinline__ void fence_regs(float (&d)[N]) {
    #pragma unroll
    for (int i = 0; i < N; i++) asm volatile("" : "+f"(d[i]) :: "memory");
}

#define K1_STAGES 3
#define K1_STAGE_BYTES 61440
#define K1_SMEM (K1_STAGES * K1_STAGE_BYTES + 1024)

__device__ __forceinline__ uint32_t hadd2_bf16(uint32_t a, uint32_t b) { uint32_t r; asm("add.rn.bf16x2 %0, %1, %2;" : "=r"(r) : "r"(a), "r"(b)); return r; }
__device__ __forceinline__ uint32_t phi_pair(uint32_t w) {
    const uint32_t p1 = hadd2_bf16(w, 0x3F803F80u);
    const uint32_t pe = pack_bf16(ex2f(bf_lo(w) * 1.4426950408889634f), ex2f(bf_hi(w) * 1.4426950408889634f));
    uint32_t m; asm("prmt.b32 %0, %1, 0, 0xBB99;" : "=r"(m) : "r"(w));
    const uint32_t r = (pe & m) | (p1 & ~m);
    return hadd2_bf16(r, 0x35863586u);
}
template<int N> __device__ __forceinline__ void phi_inplace(unsigned char* p, int tid) {
    uint4 v[N];
    #pragma unroll
    for (int i = 0; i < N; i++) v[i] = *(uint4*)(p + (i * 128 + tid) * 16);
    #pragma unroll
    for (int i = 0; i < N; i++) {
        v[i].x = phi_pair(v[i].x); v[i].y = phi_pair(v[i].y); v[i].z = phi_pair(v[i].z); v[i].w = phi_pair(v[i].w);
        *(uint4*)(p + (i * 128 + tid) * 16) = v[i];
    }
    fence_async();
}
__device__ __forceinline__ void phi36(uint32_t (&w)[36]) {
    #pragma unroll
    for (int i = 0; i < 36; i++) w[i] = phi_pair(w[i]);
}
__device__ __forceinline__ uint32_t qscale_pair(uint32_t w) {
    const float qs = 0.23570226039551584f * 1.4426950408889634f;
    return pack_bf16(bf_lo(w) * qs, bf_hi(w) * qs);
}
__device__ __forceinline__ void sts32(uint32_t addr, uint32_t v) { asm volatile("st.shared.b32 [%0], %1;" :: "r"(addr), "r"(v) : "memory"); }

__global__ void __launch_bounds__(256, 1)
qkv_kernel(const __grid_constant__ CUtensorMap mapX, const __grid_constant__ CUtensorMap mapWA, const __grid_constant__ CUtensorMap mapWA2,
           const __grid_constant__ CUtensorMap mapWB, const __grid_constant__ CUtensorMap mapWB2) {
    extern __shared__ unsigned char smem_raw[];
    __shared__ __align__(8) uint64_t bars[2 * K1_STAGES];
    __shared__ uint32_t s_nmax[12];
    const uint32_t sbase = (smem_u32(smem_raw) + 1023u) & ~1023u;
    unsigned char* stg = smem_raw + (sbase - smem_u32(smem_raw));
    const uint32_t full0 = smem_u32(bars), empty0 = full0 + 8 * K1_STAGES;
    const int mt = blockIdx.x >> 4, nt = blockIdx.x & 15;
    const int branch = nt >> 3, n0 = (nt & 7) * 216, m0 = mt * 256;
    const int wg = threadIdx.x >> 7;
    const int warp = (threadIdx.x >> 5) & 3, lane = threadIdx.x & 31, g = lane >> 2, t = lane & 3;
    TSTAMP(0, 0);
    const CUtensorMap* w1 = branch ? &mapWB : &mapWA;
    const CUtensorMap* w2 = branch ? &mapWB2 : &mapWA2;
    auto issue = [&](int kt, int part) {
        const int s = kt % K1_STAGES;
        const uint32_t st = sbase + s * K1_STAGE_BYTES, fb = full0 + 8 * s;
        if (part == 0) {
            mbar_expect_tx(fb, K1_STAGE_BYTES);
            tma_2d(st, &mapX, kt * 64, m0, fb);
            tma_2d(st + 32768 + 24576, w2, n0 + 192, kt * 64, fb);
        } else {
            tma_2d(st + 32768, w1, n0, kt * 64, fb);
            tma_2d(st + 32768 + 8192, w1, n0 + 64, kt * 64, fb);
            tma_2d(st + 32768 + 16384, w1, n0 + 128, kt * 64, fb);
        }
    };
    if (threadIdx.x == 0) {
        for (int i = 0; i < K1_STAGES; i++) { mbar_init(full0 + 8 * i, 1); mbar_init(empty0 + 8 * i, 2); }
        asm volatile("fence.mbarrier_init.release.cluster;" ::: "memory");
        issue(0, 0); issue(0, 1);
    }
    if (threadIdx.x >= 64 && threadIdx.x < 76) s_nmax[threadIdx.x - 64] = 0;
    if (blockIdx.x == 0 && threadIdx.x >= 32 && threadIdx.x < 64) g_kvflag[threadIdx.x - 32] = 0;
    __syncthreads();
    if (lane == 0 && threadIdx.x < 128) issue(1 + (threadIdx.x >> 6), (threadIdx.x >> 5) & 1);
    pdl_launch();
    const uint32_t hiA = 64u | 0x40000000u;
    const uint32_t hiB = 64u | 0x40000000u;
    const uint32_t hiB2 = 32u | 0x80000000u;
    float acc0[96], acc1[96], acd0[12], acd1[12];
    #pragma unroll
    for (int i = 0; i < 96; i++) { acc0[i] = 0.f; acc1[i] = 0.f; }
    #pragma unroll
    for (int i = 0; i < 12; i++) { acd0[i] = 0.f; acd1[i] = 0.f; }
    fence_regs(acc0); fence_regs(acc1); fence_regs(acd0); fence_regs(acd1);
    #pragma unroll 1
    for (int kt = 0; kt < 9; kt++) {
        const int s = kt % K1_STAGES;
        mbar_wait_w(full0 + 8 * s, (kt / K1_STAGES) & 1);
        const uint32_t st = sbase + s * K1_STAGE_BYTES;
        const uint32_t a_lo = ((st + wg * 16384) >> 4) | (1u << 16);
        const uint32_t b_lo = ((st + 32768) >> 4) | (512u << 16);
        const uint32_t b2_lo = ((st + 32768 + 24576) >> 4) | (1u << 16);
        WG_FENCE();
        #pragma unroll
        for (int kk = 0; kk < 4; kk++) {
            wgmma_n192_ss(acc0, mkdesc(a_lo + kk * 2, hiA), mkdesc(b_lo + kk * 128, hiB), 1);
            wgmma_n24_ss<0, 1>(acd0, mkdesc(a_lo + kk * 2, hiA), mkdesc(b2_lo + kk * 64, hiB2), 1);
            wgmma_n192_ss(acc1, mkdesc(a_lo + 512 + kk * 2, hiA), mkdesc(b_lo + kk * 128, hiB), 1);
            wgmma_n24_ss<0, 1>(acd1, mkdesc(a_lo + 512 + kk * 2, hiA), mkdesc(b2_lo + kk * 64, hiB2), 1);
        }
        WG_COMMIT();
        WG_WAIT(1);
        if (kt > 0 && kt + 2 < 9) {
            const int sp = (kt - 1) % K1_STAGES;
            if ((threadIdx.x & 127) == 0) mbar_arrive(empty0 + 8 * sp);
            if (threadIdx.x < 32) {
                mbar_wait_w(empty0 + 8 * sp, ((kt - 1) / K1_STAGES) & 1);
                if (lane == 0) { issue(kt + 2, 0); issue(kt + 2, 1); }
            }
            __syncwarp();
        }
    }
    WG_WAIT(0);
    fence_regs(acc0); fence_regs(acc1); fence_regs(acd0); fence_regs(acd1);
    TSTAMP(0, 1);
    __syncthreads();
    {
        uint32_t off9[9];
        #pragma unroll
        for (int jj = 0; jj < 9; jj++) {
            const int c = 8 * jj + 2 * t, hh = c / 18, d = c - hh * 18;
            off9[jj] = hh * 12288 + (d >> 3) * 128 + (d & 7) * 2;
        }
        const uint32_t base = sbase + (wg * 16 + warp * 2) * 384 + g * 16;
        const int k0 = branch * 3 + n0 / 576, k1 = branch * 3 + (n0 + 72) / 576, k2 = branch * 3 + (n0 + 144) / 576;
        const int row = threadIdx.x;
        const uint32_t pmagic = ((POLY_BLK >> ((row & 127) >> 3)) & 1) ? 0x46013F80u : 0x3F803F80u;
        const uint32_t pa = sbase + (row >> 3) * 384 + 256 + (row & 7) * 16 + 4;
        #pragma unroll
        for (int hh = 0; hh < 12; hh++) {
            const int kind = hh < 4 ? k0 : hh < 8 ? k1 : k2;
            sts32(pa + hh * 12288, kind == 4 ? pmagic : (kind == 2 || kind == 5) ? 0x00003F80u : 0u);
            asm volatile("st.shared.v2.b32 [%0], {%1, %1};" :: "r"(pa + hh * 12288 + 4), "r"(0u) : "memory");
        }
        auto flush = [&](int grp) {
            fence_async();
            __syncthreads();
            if (lane == 0 && threadIdx.x < 128) {
                const int hh = grp * 4 + (threadIdx.x >> 5), col0 = n0 + hh * 18;
                const int type = col0 / 576, head = (col0 % 576) / 18, kind = branch * 3 + type;
                const size_t hb = (kind == 1 || kind == 2) ? (size_t)(NH + 2 * head) * HEAD_ELEMS + mt * 12288 + (kind - 1) * 6144
                                                           : (size_t)(kind * NH + head) * HEAD_ELEMS + mt * 6144;
                asm volatile("cp.async.bulk.global.shared::cta.bulk_group [%0], [%1], %2;" :: "l"(g_T + hb), "r"(sbase + hh * 12288), "r"(12288) : "memory");
                asm volatile("cp.async.bulk.commit_group;" ::: "memory");
            }
            __syncwarp();
        };
        #pragma unroll
        for (int grp = 0; grp < 3; grp++) {
            uint32_t w[36];
            #pragma unroll
            for (int jj = 0; jj < 9; jj++) {
                const int j = grp * 9 + jj;
                if (j < 24) {
                    w[4 * jj] = pack_bf16(acc0[(4 * j) % 96], acc0[(4 * j + 1) % 96]); w[4 * jj + 1] = pack_bf16(acc0[(4 * j + 2) % 96], acc0[(4 * j + 3) % 96]);
                    w[4 * jj + 2] = pack_bf16(acc1[(4 * j) % 96], acc1[(4 * j + 1) % 96]); w[4 * jj + 3] = pack_bf16(acc1[(4 * j + 2) % 96], acc1[(4 * j + 3) % 96]);
                } else {
                    w[4 * jj] = pack_bf16(acd0[(4 * j) % 12], acd0[(4 * j + 1) % 12]); w[4 * jj + 1] = pack_bf16(acd0[(4 * j + 2) % 12], acd0[(4 * j + 3) % 12]);
                    w[4 * jj + 2] = pack_bf16(acd1[(4 * j) % 12], acd1[(4 * j + 1) % 12]); w[4 * jj + 3] = pack_bf16(acd1[(4 * j + 2) % 12], acd1[(4 * j + 3) % 12]);
                }
            }
            if (grp == 0 ? k0 == 1 : (grp == 2 && k2 == 1 && k1 != 1)) phi36(w);
            #pragma unroll
            for (int jj = 0; jj < 9; jj++) {
                const uint32_t a = base + grp * 49152 + off9[jj];
                sts32(a, w[4 * jj]); sts32(a + 384, w[4 * jj + 1]); sts32(a + 3072, w[4 * jj + 2]); sts32(a + 3456, w[4 * jj + 3]);
            }
            flush(grp);
        }
        TSTAMP(0, 3);
        #pragma unroll 1
        for (int grp = 0; grp < 3; grp++) {
            if ((grp == 0 ? k0 : grp == 1 ? k1 : k2) == 4) {
                #pragma unroll 2
                for (int hq = 0; hq < 4; hq++) {
                    const unsigned char* src = stg + (grp * 4 + hq) * 12288 + (row >> 3) * 384 + (row & 7) * 16;
                    const uint4 v0 = *(const uint4*)src, v1 = *(const uint4*)(src + 128);
                    const uint32_t w[9] = {v0.x, v0.y, v0.z, v0.w, v1.x, v1.y, v1.z, v1.w, *(const uint32_t*)(src + 256)};
                    float n2 = 0.f;
                    #pragma unroll
                    for (int i = 0; i < 9; i++) { const float a = bf_lo(w[i]), b = bf_hi(w[i]); n2 = fmaf(a, a, n2); n2 = fmaf(b, b, n2); }
                    uint32_t nb = __float_as_uint(n2);
                    if (!(n2 >= 0.f)) nb = 0x7F800000u;
                    nb = __reduce_max_sync(0xFFFFFFFFu, nb);
                    if (lane == 0) atomicMax(&s_nmax[grp * 4 + hq], nb);
                }
            }
        }
        __syncthreads();
        if (threadIdx.x < 12) {
            const int col0 = n0 + threadIdx.x * 18;
            if (branch == 1 && col0 / 576 == 1) g_kmax[mt][(col0 % 576) / 18] = __uint_as_float(s_nmax[threadIdx.x]);
        }
        if (lane == 0 && threadIdx.x < 128) asm volatile("cp.async.bulk.wait_group.read 0;" ::: "memory");
    }
    TSTAMP(0, 2);
}

__device__ __forceinline__ uint32_t hfma2(uint32_t a, uint32_t b, uint32_t c) { uint32_t r; asm("fma.rn.f16x2 %0, %1, %2, %3;" : "=r"(r) : "r"(a), "r"(b), "r"(c)); return r; }
__device__ __forceinline__ uint32_t and_or(uint32_t a, uint32_t m, uint32_t o) { uint32_t r; asm("lop3.b32 %0, %1, %2, %3, 0xEA;" : "=r"(r) : "r"(a), "r"(m), "r"(o)); return r; }
__device__ __forceinline__ uint32_t poly_ex2_pair(float t0, float t1) {
    const uint32_t u = __byte_perm(__float_as_uint(t0), __float_as_uint(t1), 0x5410);
    const uint32_t m = and_or(u, 0x03FF03FFu, 0x3C003C00u);
    uint32_t y = hfma2(m, 0x2CFE2CFEu, 0xA019A019u);
    y = hfma2(y, m, 0xB82EB82Eu);
    y = hfma2(y, m, 0x3FCF3FCFu);
    const uint32_t w = u + y + 0xC203C204u;
    return and_or(w >> 3, 0x1FFF1FFFu, 0x20002000u);
}

template<int B0, int NB>
__device__ __forceinline__ void softmax_blocks(float (&s)[64], uint32_t (&p)[32]) {
    #pragma unroll
    for (int i = B0 * 4; i < (B0 + NB) * 4; i++) asm volatile("" : "+f"(s[i]) :: "memory");
    #pragma unroll
    for (int b = B0; b < B0 + NB; b++) {
        if ((POLY_BLK >> b) & 1) {
            p[2 * b + 0] = poly_ex2_pair(s[4 * b], s[4 * b + 1]);
            p[2 * b + 1] = poly_ex2_pair(s[4 * b + 2], s[4 * b + 3]);
        } else {
            p[2 * b + 0] = pack_bf16(ex2f(s[4 * b]), ex2f(s[4 * b + 1]));
            p[2 * b + 1] = pack_bf16(ex2f(s[4 * b + 2]), ex2f(s[4 * b + 3]));
        }
    }
}

__device__ __forceinline__ void store_o(int branch, int row0, int h, int t, const float (&o)[12], float r0, float r1) {
    uint32_t* p = (uint32_t*)g_O + ((((branch * 16 + (row0 >> 7)) * 8 + (h >> 2)) * 16 + ((row0 >> 3) & 15)) * 72 + (row0 & 7)) * 4;
    uint32_t* q = p + (h & 3) * 64 + t;
    q[0] = pack_bf16(o[0] * r0, o[1] * r0); q[288] = pack_bf16(o[2] * r1, o[3] * r1);
    q[32] = pack_bf16(o[4] * r0, o[5] * r0); q[288 + 32] = pack_bf16(o[6] * r1, o[7] * r1);
    if (t == 0) { p[256 + (h & 3)] = pack_bf16(o[8] * r0, o[9] * r0); p[288 + 256 + (h & 3)] = pack_bf16(o[10] * r1, o[11] * r1); }
}

#define K2_SMEM (2 * HEAD_BYTES + 24576 + 1536 + 1024)

__global__ void __launch_bounds__(512, 1)
attn_kernel(const __nv_bfloat16* __restrict__ x, const __nv_bfloat16* __restrict__ gate_w,
            const __nv_bfloat16* __restrict__ woA, const __nv_bfloat16* __restrict__ woB) {
    extern __shared__ unsigned char smem_raw[];
    __shared__ __align__(8) uint64_t bars[16];
    const uint32_t sK = (smem_u32(smem_raw) + 1023u) & ~1023u;
    const uint32_t sV = sK + HEAD_BYTES;
    unsigned char* sgen = smem_raw + (sK - smem_u32(smem_raw));
    TSTAMP(1, 0);
    const uint32_t bar0 = smem_u32(bars);
    const int wg = threadIdx.x >> 7, warp = (threadIdx.x >> 5) & 3, lane = threadIdx.x & 31, g = lane >> 2, t = lane & 3;
    if (threadIdx.x == 0) {
        for (int i = 0; i < 16; i++) mbar_init(bar0 + 8 * i, 1);
        asm volatile("fence.mbarrier_init.release.cluster;" ::: "memory");
    }
    __syncthreads();
    pdl_launch();
    const uint32_t kd0 = (sK >> 4) | (8u << 16);
    const uint32_t kd1 = ((sK + 256) >> 4);
    const uint32_t khi = 24;
    const uint32_t vd0 = (sV >> 4) | (24u << 16);
    const uint32_t vhi = 8;

    if (blockIdx.x < 4) {
        const int w16 = blockIdx.x * 4 + wg;
        const int hd0 = w16 < 8 ? w16 : w16 < 12 ? w16 + 8 : w16 + 16, hd1 = w16 < 8 ? w16 + 8 : w16 + 12;
        const int tid = threadIdx.x & 127;
        {
            if (threadIdx.x < 8) asm volatile("cp.async.bulk.prefetch.L2.global [%0], %1;" :: "l"((const char*)((blockIdx.x & 1) ? woB : woA) + ((blockIdx.x >> 1) * 8 + threadIdx.x) * 41472), "r"(41472) : "memory");
            uint32_t gv[9];
            #pragma unroll
            for (int i = 0; i < 9; i++) gv[i] = ((const uint32_t*)gate_w)[lane + 32 * i];
            #pragma unroll 1
            for (int r = blockIdx.x * 512 + (threadIdx.x >> 5) * 8; r < blockIdx.x * 512 + 512; r += 128) {
                uint32_t xv[8][9];
                #pragma unroll
                for (int q = 0; q < 8; q++) {
                    #pragma unroll
                    for (int i = 0; i < 9; i++) xv[q][i] = ((const uint32_t*)(x + (size_t)(r + q) * DM))[lane + 32 * i];
                }
                float sum[8];
                #pragma unroll
                for (int q = 0; q < 8; q++) {
                    sum[q] = 0.f;
                    #pragma unroll
                    for (int i = 0; i < 9; i++) sum[q] += bfr(bf_lo(xv[q][i]) * bf_lo(gv[i])) + bfr(bf_hi(xv[q][i]) * bf_hi(gv[i]));
                }
                #pragma unroll
                for (int o = 16; o > 0; o >>= 1) {
                    #pragma unroll
                    for (int q = 0; q < 8; q++) sum[q] += __shfl_xor_sync(~0u, sum[q], o);
                }
                float z = sum[0];
                #pragma unroll
                for (int q = 1; q < 8; q++) z = lane == q ? sum[q] : z;
                if (lane < 8) g_gate[r + lane] = bfr(1.0f / (1.0f + __expf(-bfr(z))));
            }
        }
        TSTAMP(1, 3);
        pdl_wait();
        TSTAMP(1, 1);
        const uint32_t slot0 = sK + wg * 49152, fb0 = bar0 + wg * 16;
        auto issue = [&](int c) {
            mbar_expect_tx(fb0 + 8 * (c & 1), 24576);
            bulk_g2s(slot0 + (c & 1) * 24576, (const char*)(g_T + (size_t)(NH + 2 * (c < 8 ? hd0 : hd1)) * HEAD_ELEMS) + (size_t)(c & 7) * 24576, 24576, fb0 + 8 * (c & 1));
        };
        if (tid == 0) { issue(0); issue(1); }
        #pragma unroll 1
        for (int hi = 0; hi < 2; hi++) {
            float d1[4][12];
            #pragma unroll
            for (int k = 0; k < 4; k++) {
                #pragma unroll
                for (int i = 0; i < 12; i++) d1[k][i] = 0.f;
                fence_regs(d1[k]);
            }
            #pragma unroll 1
            for (int cc = 0; cc < 8; cc++) {
                const int c = hi * 8 + cc;
                mbar_wait_w(fb0 + 8 * (c & 1), (c >> 1) & 1);
                if (hi == 1) {
                    unsigned char* p = sgen + wg * 49152 + (c & 1) * 24576 + (tid >> 3) * 384 + (tid & 7) * 16;
                    uint4 v0 = *(uint4*)p, v1 = *(uint4*)(p + 128), v2 = *(uint4*)(p + 6144), v3 = *(uint4*)(p + 6144 + 128);
                    uint32_t w0 = *(uint32_t*)(p + 256), w1 = *(uint32_t*)(p + 6144 + 256);
                    v0.x = phi_pair(v0.x); v0.y = phi_pair(v0.y); v0.z = phi_pair(v0.z); v0.w = phi_pair(v0.w);
                    v1.x = phi_pair(v1.x); v1.y = phi_pair(v1.y); v1.z = phi_pair(v1.z); v1.w = phi_pair(v1.w);
                    v2.x = phi_pair(v2.x); v2.y = phi_pair(v2.y); v2.z = phi_pair(v2.z); v2.w = phi_pair(v2.w);
                    v3.x = phi_pair(v3.x); v3.y = phi_pair(v3.y); v3.z = phi_pair(v3.z); v3.w = phi_pair(v3.w);
                    *(uint4*)p = v0; *(uint4*)(p + 128) = v1; *(uint4*)(p + 6144) = v2; *(uint4*)(p + 6144 + 128) = v3;
                    *(uint32_t*)(p + 256) = phi_pair(w0); *(uint32_t*)(p + 6144 + 256) = phi_pair(w1);
                    fence_async();
                    named_bar(1 + wg, 128);
                }
                const uint32_t base = ((slot0 + (c & 1) * 24576) >> 4) | (24u << 16);
                WG_FENCE();
                #pragma unroll
                for (int ks = 0; ks < 16; ks++)
                    wgmma_n24_ss<1, 1>(d1[ks & 3], mkdesc(base + ks * 48, 8u), mkdesc(base + 768 + ks * 48, vhi), 1);
                WG_COMMIT();
                WG_WAIT(0);
                named_bar(1 + wg, 128);
                if (tid == 0 && c + 2 < 16) issue(c + 2);
            }
            #pragma unroll
            for (int k = 0; k < 4; k++) fence_regs(d1[k]);
            #pragma unroll
            for (int i = 0; i < 12; i++) d1[0][i] = (d1[0][i] + d1[1][i]) + (d1[2][i] + d1[3][i]);
            if (warp < 2) {
                const int d = warp * 16 + g;
                uint32_t* kp = (uint32_t*)(g_kv + (hi ? hd1 : hd0) * 768 + (d >> 3) * 192 + (d & 7) * 8 + 2 * t);
                #pragma unroll
                for (int j = 0; j < 3; j++) {
                    kp[32 * j] = d < 18 ? pack_bf16(d1[0][4 * j], d1[0][4 * j + 1]) : 0u;
                    kp[96 + 32 * j] = warp == 0 ? pack_bf16(d1[0][4 * j + 2], d1[0][4 * j + 3]) : 0u;
                }
                __threadfence();
            }
            named_bar(1 + wg, 128);
            if (tid == 0) asm volatile("st.release.gpu.global.b32 [%0], %1;" :: "l"(g_kvflag + (hi ? hd1 : hd0)), "r"(1) : "memory");
        }
        TSTAMP(1, 4);
        TSTAMP(1, 2);
        return;
    }
    const int cta = blockIdx.x - 4;

    {
        constexpr int PER = 82944 / 128, NQ = (PER + 511) / 512;
        uint4 wv[NQ];
        #pragma unroll
        for (int q = 0; q < NQ; q++) {
            const int id = cta * PER + threadIdx.x + q * 512;
            if (threadIdx.x + q * 512 < PER) wv[q] = *(const uint4*)((id >= 41472 ? woB - 41472 * 8 : woA) + (size_t)id * 8);
        }
        #pragma unroll
        for (int q = 0; q < NQ; q++) {
            const int id = cta * PER + threadIdx.x + q * 512;
            const int b = id >= 41472, r2 = id - b * 41472, k = r2 / 72, c = r2 % 72;
            const int hh = k / 18, d = k % 18;
            const int kp = (hh >> 2) * 72 + (d < 16 ? (hh & 3) * 16 + d : 64 + (hh & 3) * 2 + (d - 16));
            if (threadIdx.x + q * 512 < PER) *(uint4*)(g_Wt + ((((c / 24) * 2 + b) * 8 + kp / 72) * 24 + (c % 24)) * 576 + (kp % 72) * 8) = wv[q];
        }
    }

    const int h = cta >> 2, quarter = cta & 3;
    const uint32_t sPQ = sK + 2 * HEAD_BYTES, sKVt = sPQ + 24576;
    pdl_wait();
    TSTAMP(1, 1);
    auto issue_kv = [&](int c) {
        mbar_expect_tx(bar0 + 8 * c, 24576);
        bulk_g2s(sK + c * 12288, (const char*)(g_T + (size_t)(4 * NH + h) * HEAD_ELEMS) + c * 12288, 12288, bar0 + 8 * c);
        bulk_g2s(sV + c * 12288, (const char*)(g_T + (size_t)(5 * NH + h) * HEAD_ELEMS) + c * 12288, 12288, bar0 + 8 * c);
    };
    int kv_state = 0;
    auto kv_poll = [&](bool block) {
        if (threadIdx.x == 0 && kv_state != 2) {
            while (block && kv_state == 0) asm volatile("ld.acquire.gpu.global.b32 %0, [%1];" : "=r"(kv_state) : "l"(g_kvflag + h) : "memory");
            if (kv_state == 1) {
                asm volatile("fence.proxy.async.global;" ::: "memory");
                mbar_expect_tx(bar0 + 72, 1536);
                bulk_g2s(sKVt, g_kv + h * 768, 1536, bar0 + 72);
                kv_state = 2;
            } else {
                asm volatile("ld.acquire.gpu.global.b32 %0, [%1];" : "=r"(kv_state) : "l"(g_kvflag + h) : "memory");
            }
        }
    };
    float km2 = 0.f;
    #pragma unroll
    for (int i = 0; i < 8; i++) km2 = fmaxf(km2, g_kmax[i][h]);
    int s_fast_tmp = 0;
    uint32_t zr = 0u;
    asm volatile("" : "+r"(zr));
    uint32_t qf[2][6];
    #pragma unroll
    for (int pass = 0; pass < 2; pass++) {
        const int row0 = quarter * 512 + (wg * 2 + pass) * 64 + warp * 16 + g;
        const uint32_t* q0 = (const uint32_t*)(g_T + (size_t)(3 * NH + h) * HEAD_ELEMS + (row0 >> 3) * 192 + (row0 & 7) * 8) + t;
        qf[pass][0] = q0[0]; qf[pass][1] = q0[96]; qf[pass][2] = q0[32]; qf[pass][3] = q0[128];
        qf[pass][4] = q0[64]; qf[pass][5] = q0[160];
    }
    if (threadIdx.x == 0) issue_kv(0);
    if (threadIdx.x == 128) issue_kv(1);
    __syncwarp();
    #pragma unroll
    for (int i = 0; i < 6; i++) { qf[0][i] = qscale_pair(qf[0][i]); qf[1][i] = qscale_pair(qf[1][i]); }
    float mrow[2][2];
    bool ok = true;
    #pragma unroll
    for (int pass = 0; pass < 2; pass++) {
        auto sq = [](uint32_t v) { float a = bf_lo(v), b = bf_hi(v); return a * a + b * b; };
        float n0 = sq(qf[pass][0]) + sq(qf[pass][2]) + sq(qf[pass][4]);
        float n1 = sq(qf[pass][1]) + sq(qf[pass][3]) + sq(qf[pass][5]);
        n0 += __shfl_xor_sync(~0u, n0, 1); n0 += __shfl_xor_sync(~0u, n0, 2);
        n1 += __shfl_xor_sync(~0u, n1, 1); n1 += __shfl_xor_sync(~0u, n1, 2);
        mrow[pass][0] = sqrtf(n0 * km2) * 1.01f + 0.01f;
        mrow[pass][1] = sqrtf(n1 * km2) * 1.01f + 0.01f;
        ok = ok && (mrow[pass][0] <= 31.0f) && (mrow[pass][1] <= 31.0f);
    }
    bool fast;
    asm volatile("{\n.reg .pred p, q;\nsetp.ne.b32 p, %1, 0;\nbar.red.and.pred q, %2, 128, p;\nselp.b32 %0, 1, 0, q;\n}\n"
                 : "=r"(*(int*)&s_fast_tmp) : "r"((int)ok), "r"(1 + wg) : "memory");
    fast = __all_sync(0xFFFFFFFFu, s_fast_tmp != 0);
    TSTAMP(1, 3);

    #pragma unroll 1
    for (int pass = 0; pass < 2; pass++) {
        const int row0 = quarter * 512 + (wg * 2 + pass) * 64 + warp * 16 + g;
        uint32_t qa[6];
        #pragma unroll
        for (int i = 0; i < 6; i++) qa[i] = pass ? qf[1][i] : qf[0][i];
        float o[12];
        #pragma unroll
        for (int i = 0; i < 12; i++) o[i] = 0.f;
        fence_regs(o);
        float s[64]; uint32_t p[32];
        #pragma unroll
        for (int i = 0; i < 64; i++) s[i] = 0.f;
        fence_regs(s);
        if (fast) {
            if (t == 1) { qa[4] = pack_bf16(-(pass ? mrow[1][0] : mrow[0][0]), 1.0f); qa[5] = pack_bf16(-(pass ? mrow[1][1] : mrow[0][1]), 1.0f); }
            #pragma unroll 1
            for (int j = 0; j < 16; j++) {
                if (pass == 0 && (j & 1) == 0) {
                    const int cn = (j >> 1) + 2;
                    if ((threadIdx.x & 127) == 0 && (cn & 3) == wg) {
                        if (cn < 8) issue_kv(cn);
                        else if (cn == 8) { mbar_expect_tx(bar0 + 64, 24576); bulk_g2s(sPQ, (const char*)(g_T + (size_t)h * HEAD_ELEMS) + quarter * 24576, 24576, bar0 + 64); }
                    }
                    mbar_wait_w(bar0 + 8 * (j >> 1), 0);
                }
                const uint32_t ko = j * 384;
                WG_FENCE();
                wgmma_n128_rs<0>(s, qa[0], qa[1], qa[2], qa[3], mkdesc(kd0 + ko, khi));
                wgmma_n128_rs<1>(s, qa[4], qa[5], zr, zr, mkdesc(kd1 + ko, khi));
                WG_COMMIT();
                if (pass == 1 && (j & 3) == 3) { kv_poll(false); __syncwarp(); }
                WG_WAIT(0);
                #pragma unroll
                for (int qd = 0; qd < 4; qd++) {
                    if (qd == 0) softmax_blocks<0, 4>(s, p);
                    if (qd == 1) softmax_blocks<4, 4>(s, p);
                    if (qd == 2) softmax_blocks<8, 4>(s, p);
                    if (qd == 3) softmax_blocks<12, 4>(s, p);
                    WG_FENCE();
                    wgmma_n24_rs(o, p[qd * 8 + 0], p[qd * 8 + 1], p[qd * 8 + 2], p[qd * 8 + 3], mkdesc(vd0 + ko + qd * 96, vhi));
                    wgmma_n24_rs(o, p[qd * 8 + 4], p[qd * 8 + 5], p[qd * 8 + 6], p[qd * 8 + 7], mkdesc(vd0 + ko + qd * 96 + 48, vhi));
                    WG_COMMIT();
                }
                WG_WAIT(0);
            }
        } else {
            {
                const uint32_t* q0 = (const uint32_t*)(g_T + (size_t)(3 * NH + h) * HEAD_ELEMS + (row0 >> 3) * 192 + (row0 & 7) * 8) + t;
                qa[0] = q0[0]; qa[1] = q0[96]; qa[2] = q0[32]; qa[3] = q0[128]; qa[4] = q0[64]; qa[5] = q0[160];
            }
            const float qs = 0.23570226039551584f * 1.4426950408889634f;
            float mr0 = -INFINITY, mr1 = -INFINITY;
            #pragma unroll 1
            for (int j = 0; j < 16; j++) {
                if (pass == 0 && (j & 1) == 0) {
                    const int cn = (j >> 1) + 2;
                    if ((threadIdx.x & 127) == 0 && (cn & 3) == wg) {
                        if (cn < 8) issue_kv(cn);
                        else if (cn == 8) { mbar_expect_tx(bar0 + 64, 24576); bulk_g2s(sPQ, (const char*)(g_T + (size_t)h * HEAD_ELEMS) + quarter * 24576, 24576, bar0 + 64); }
                    }
                    mbar_wait_w(bar0 + 8 * (j >> 1), 0);
                }
                const uint32_t ko = j * 384;
                WG_FENCE();
                wgmma_n128_rs<0>(s, qa[0], qa[1], qa[2], qa[3], mkdesc(kd0 + ko, khi));
                wgmma_n128_rs<1>(s, qa[4], qa[5], zr, zr, mkdesc(kd1 + ko, khi));
                WG_COMMIT();
                WG_WAIT(0);
                fence_regs(s); fence_regs(o);
                float x0 = mr0, x1 = mr1;
                #pragma unroll
                for (int b = 0; b < 16; b++) {
                    x0 = fmaxf(x0, fmaxf(s[4 * b], s[4 * b + 1]));
                    x1 = fmaxf(x1, fmaxf(s[4 * b + 2], s[4 * b + 3]));
                }
                x0 = fmaxf(x0, __shfl_xor_sync(~0u, x0, 1)); x0 = fmaxf(x0, __shfl_xor_sync(~0u, x0, 2));
                x1 = fmaxf(x1, __shfl_xor_sync(~0u, x1, 1)); x1 = fmaxf(x1, __shfl_xor_sync(~0u, x1, 2));
                const float c0 = exp2f((mr0 - x0) * qs), c1 = exp2f((mr1 - x1) * qs);
                mr0 = x0; mr1 = x1;
                #pragma unroll
                for (int i = 0; i < 12; i++) o[i] *= (i & 2) ? c1 : c0;
                #pragma unroll
                for (int b = 0; b < 16; b++) {
                    p[2 * b] = pack_bf16(exp2f((s[4 * b] - x0) * qs), exp2f((s[4 * b + 1] - x0) * qs));
                    p[2 * b + 1] = pack_bf16(exp2f((s[4 * b + 2] - x1) * qs), exp2f((s[4 * b + 3] - x1) * qs));
                }
                fence_regs(o);
                WG_FENCE();
                #pragma unroll
                for (int kk = 0; kk < 8; kk++)
                    wgmma_n24_rs(o, p[kk * 4 + 0], p[kk * 4 + 1], p[kk * 4 + 2], p[kk * 4 + 3], mkdesc(vd0 + ko + kk * 48, vhi));
                WG_COMMIT();
                WG_WAIT(0);
            }
        }
        fence_regs(o);
        const float l0 = __shfl_sync(~0u, o[8], (lane & ~3) | 1);
        const float l1 = __shfl_sync(~0u, o[10], (lane & ~3) | 1);
        store_o(1, row0, h, t, o, 1.0f / l0, 1.0f / l1);
    }
    TSTAMP(1, 4);
    {
        kv_poll(true); kv_poll(true);
        mbar_wait_w(bar0 + 64, 0);
        phi_inplace<3>(sgen + 2 * HEAD_BYTES + wg * 6144, threadIdx.x & 127);
        named_bar(1 + wg, 128);
        mbar_wait_w(bar0 + 72, 0);
        float e[4][12];
        #pragma unroll
        for (int k = 0; k < 4; k++) {
            #pragma unroll
            for (int i = 0; i < 12; i++) e[k][i] = 0.f;
            fence_regs(e[k]);
        }
        const uint32_t ab = (sPQ + wg * 6144) >> 4, bb = (sKVt >> 4) | (24u << 16);
        WG_FENCE();
        wgmma_n24_ss<0, 1>(e[0], mkdesc(ab | (8u << 16), khi), mkdesc(bb, vhi), 0);
        wgmma_n24_ss<0, 1>(e[1], mkdesc((ab + 192) | (8u << 16), khi), mkdesc(bb, vhi), 0);
        wgmma_n24_ss<0, 1>(e[2], mkdesc(ab + 16, khi), mkdesc(bb + 48, vhi), 0);
        wgmma_n24_ss<0, 1>(e[3], mkdesc(ab + 192 + 16, khi), mkdesc(bb + 48, vhi), 0);
        WG_COMMIT();
        WG_WAIT(0);
        #pragma unroll
        for (int k = 0; k < 4; k++) fence_regs(e[k]);
        #pragma unroll
        for (int m = 0; m < 2; m++) {
            #pragma unroll
            for (int i = 0; i < 12; i++) e[m][i] = bfr(e[m][i] + e[m + 2][i]);
            const float l0 = __shfl_sync(~0u, e[m][8], (lane & ~3) | 1), l1 = __shfl_sync(~0u, e[m][10], (lane & ~3) | 1);
            store_o(0, quarter * 512 + (wg * 2 + m) * 64 + warp * 16 + g, h, t, e[m], 1.0f / bfr(l0 + 1e-6f), 1.0f / bfr(l1 + 1e-6f));
        }
    }
    TSTAMP(1, 2);
}

#define K3_UNITS 4
#define K3_UNIT_BYTES 46080
#define K3_SMEM (K3_UNITS * K3_UNIT_BYTES + 26624 + 1024)

__global__ void __cluster_dims__(2, 1, 1) __launch_bounds__(288, 1)
out_kernel(__nv_bfloat16* __restrict__ out) {
    extern __shared__ unsigned char smem_raw[];
    __shared__ __align__(8) uint64_t bars[2 * K3_UNITS + 8];
    const uint32_t sA = (smem_u32(smem_raw) + 1023u) & ~1023u;
    const uint32_t sX = sA + K3_UNITS * K3_UNIT_BYTES;
    const uint32_t full0 = smem_u32(bars), empty0 = full0 + 8 * K3_UNITS;
    const int br = blockIdx.x & 1, tile = blockIdx.x >> 1, mt = tile / 3, nt = tile % 3;
    const int m0 = mt * 128, n0 = nt * 192;
    TSTAMP(2, 0);
    if (threadIdx.x == 0) {
        for (int i = 0; i < K3_UNITS; i++) { mbar_init(full0 + 8 * i, 1); mbar_init(empty0 + 8 * i, 2); }
        for (int i = 0; i < 8; i++) mbar_init(full0 + 16 * K3_UNITS + 8 * i, 1);
        asm volatile("fence.mbarrier_init.release.cluster;" ::: "memory");
    }
    __syncthreads();
    cluster_arrive();
    TSTAMP(2, 3);
    pdl_wait();
    TSTAMP(2, 1);
    const int wg = threadIdx.x >> 7;
    if (wg == 2) {
        if (threadIdx.x == 256) {
            for (int c = 0; c < 8; c++) {
                const int s = c % K3_UNITS;
                if (c >= K3_UNITS) mbar_wait(empty0 + 8 * s, 0);
                const uint32_t st = sA + s * K3_UNIT_BYTES;
                mbar_expect_tx(full0 + 8 * s, K3_UNIT_BYTES);
                bulk_g2s(st, g_O + (size_t)((br * 16 + mt) * 8 + c) * 9216, 18432, full0 + 8 * s);
                bulk_g2s(st + 18432, g_Wt + (size_t)((nt * 2 + br) * 8 + c) * 13824, 27648, full0 + 8 * s);
            }
        }
        __syncwarp();
        cluster_wait();
        cluster_arrive();
    } else {
        const int warp = (threadIdx.x >> 5) & 3, lane = threadIdx.x & 31, g = lane >> 2, t = lane & 3;
        float acc[96];
        #pragma unroll
        for (int i = 0; i < 96; i++) acc[i] = 0.f;
        fence_regs(acc);
        const uint32_t hiA = 72u;
        const uint32_t hiB = 72u;
        const int r0 = m0 + wg * 64 + warp * 16 + g;
        float g0 = g_gate[r0], g1 = g_gate[r0 + 8];
        if (br) { g0 = bfr(1.0f - g0); g1 = bfr(1.0f - g1); }
        #pragma unroll 1
        for (int pr = 0; pr < 4; pr++) {
            const int s = (pr & 1) * 2;
            const uint32_t a_lo = ((sA + s * K3_UNIT_BYTES + wg * 9216) & 0x3FFFF) >> 4;
            const uint32_t b_lo = ((sA + s * K3_UNIT_BYTES + 18432) & 0x3FFFF) >> 4;
            mbar_wait_w(full0 + 8 * s, pr >> 1);
            if (pr == 0) TSTAMP(2, 4);
            WG_FENCE();
            #pragma unroll
            for (int i = 0; i < 4; i++) wgmma_n192_ss(acc, mkdesc((a_lo + i * 16) | (8u << 16), hiA), mkdesc((b_lo + i * 16) | (8u << 16), hiB), 1);
            WG_COMMIT();
            mbar_wait_w(full0 + 8 * s + 8, pr >> 1);
            WG_FENCE();
            wgmma_n192_ss(acc, mkdesc((a_lo + 64) | ((K3_UNIT_BYTES / 16 - 64) << 16), hiA), mkdesc((b_lo + 64) | ((K3_UNIT_BYTES / 16 - 64) << 16), hiB), 1);
            #pragma unroll
            for (int i = 0; i < 4; i++)
                wgmma_n192_ss(acc, mkdesc((a_lo + K3_UNIT_BYTES / 16 + 8 + i * 16) | (8u << 16), hiA), mkdesc((b_lo + K3_UNIT_BYTES / 16 + 8 + i * 16) | (8u << 16), hiB), 1);
            WG_COMMIT();
            if (pr < 2) {
                WG_WAIT(0);
                if ((threadIdx.x & 127) < 2) mbar_arrive(empty0 + 8 * (s + (threadIdx.x & 1)));
            }
        }
        WG_WAIT(0);
        fence_regs(acc);
        TSTAMP(2, 5);
        uint32_t keep[24];
        named_bar(1, 256);
        const uint32_t snd = sA + (wg * 4 + warp) * 3328;
        #pragma unroll
        for (int j = 0; j < 24; j++) {
            const uint32_t v0 = pack_bf16(g0 * bfr(acc[4 * j]), g0 * bfr(acc[4 * j + 1]));
            const uint32_t v1 = pack_bf16(g1 * bfr(acc[4 * j + 2]), g1 * bfr(acc[4 * j + 3]));
            const int jj = j % 12;
            if ((j < 12) == (br == 0)) { keep[2 * jj] = v0; keep[2 * jj + 1] = v1; }
            else { sts32(snd + g * 208 + jj * 16 + t * 4, v0); sts32(snd + (g + 8) * 208 + jj * 16 + t * 4, v1); }
        }
        fence_async();
        __syncwarp();
        cluster_wait();
        const uint32_t xbar = full0 + 16 * K3_UNITS + 8 * (wg * 4 + warp);
        if (lane == 0) {
            uint32_t rdst, rbar;
            asm volatile("mapa.shared::cluster.u32 %0, %1, %2;" : "=r"(rdst) : "r"(sX + (wg * 4 + warp) * 3328), "r"(br ^ 1));
            asm volatile("mapa.shared::cluster.u32 %0, %1, %2;" : "=r"(rbar) : "r"(xbar), "r"(br ^ 1));
            mbar_expect_tx(xbar, 3328);
            asm volatile("cp.async.bulk.shared::cluster.shared::cta.mbarrier::complete_tx::bytes [%0], [%1], %2, [%3];"
                         :: "r"(rdst), "r"(snd), "r"(3328), "r"(rbar) : "memory");
        }
        mbar_wait_w(xbar, 0);
        cluster_arrive();
        const uint32_t sx = sX + (wg * 64 + warp * 16) * 208;
        #pragma unroll
        for (int jj = 0; jj < 12; jj++) {
            uint32_t p0, p1;
            asm volatile("ld.shared.b32 %0, [%1];" : "=r"(p0) : "r"(sx + g * 208 + jj * 16 + t * 4));
            asm volatile("ld.shared.b32 %0, [%1];" : "=r"(p1) : "r"(sx + (g + 8) * 208 + jj * 16 + t * 4));
            sts32(sx + g * 208 + jj * 16 + t * 4, hadd2_bf16(keep[2 * jj], p0));
            sts32(sx + (g + 8) * 208 + jj * 16 + t * 4, hadd2_bf16(keep[2 * jj + 1], p1));
        }
        __syncwarp();
        #pragma unroll
        for (int i = 0; i < 6; i++) {
            const int id = i * 32 + lane, r = id / 12, c = id % 12;
            uint4 v;
            asm volatile("ld.shared.v4.b32 {%0,%1,%2,%3}, [%4];" : "=r"(v.x), "=r"(v.y), "=r"(v.z), "=r"(v.w) : "r"(sx + r * 208 + c * 16));
            *(uint4*)(out + (size_t)(m0 + wg * 64 + warp * 16 + r) * DM + n0 + br * 96 + c * 8) = v;
        }
        TSTAMP(2, 2);
    }
    cluster_wait();
}

typedef CUresult (*EncodeFn)(CUtensorMap*, CUtensorMapDataType, cuuint32_t, void*, const cuuint64_t*, const cuuint64_t*,
                             const cuuint32_t*, const cuuint32_t*, CUtensorMapInterleave, CUtensorMapSwizzle,
                             CUtensorMapL2promotion, CUtensorMapFloatOOBfill);

static void make_map(EncodeFn enc, CUtensorMap* m, const void* base, uint64_t inner, uint64_t outer, uint32_t box_in, uint32_t box_out, CUtensorMapSwizzle sw) {
    cuuint64_t dims[2] = {inner, outer};
    cuuint64_t strides[1] = {inner * 2};
    cuuint32_t box[2] = {box_in, box_out};
    cuuint32_t es[2] = {1, 1};
    enc(m, CU_TENSOR_MAP_DATA_TYPE_BFLOAT16, 2, (void*)base, dims, strides, box, es, CU_TENSOR_MAP_INTERLEAVE_NONE, sw,
        CU_TENSOR_MAP_L2_PROMOTION_L2_256B, CU_TENSOR_MAP_FLOAT_OOB_FILL_NONE);
}

extern "C" void kernel_launch(void* const* d_in, const int* in_sizes, int n_in, void* d_out, int out_size) {
    const __nv_bfloat16* x = (const __nv_bfloat16*)d_in[0];
    const __nv_bfloat16* wA = (const __nv_bfloat16*)d_in[1];
    const __nv_bfloat16* woA = (const __nv_bfloat16*)d_in[2];
    const __nv_bfloat16* wB = (const __nv_bfloat16*)d_in[4];
    const __nv_bfloat16* woB = (const __nv_bfloat16*)d_in[5];
    const __nv_bfloat16* gw = (const __nv_bfloat16*)d_in[6];
    __nv_bfloat16* out = (__nv_bfloat16*)d_out;

    static EncodeFn enc = nullptr;
    if (!enc) {
        void* fn = nullptr; cudaDriverEntryPointQueryResult st;
        cudaGetDriverEntryPoint("cuTensorMapEncodeTiled", &fn, cudaEnableDefault, &st);
        enc = (EncodeFn)fn;
        cudaFuncSetAttribute(qkv_kernel, cudaFuncAttributeMaxDynamicSharedMemorySize, K1_SMEM);
        cudaFuncSetAttribute(attn_kernel, cudaFuncAttributeMaxDynamicSharedMemorySize, K2_SMEM);
        cudaFuncSetAttribute(out_kernel, cudaFuncAttributeMaxDynamicSharedMemorySize, K3_SMEM);
    }
    CUtensorMap mX, mWA, mWA2, mWB, mWB2;
    make_map(enc, &mX, x, DM, S_LEN, 64, 256, CU_TENSOR_MAP_SWIZZLE_128B);
    make_map(enc, &mWA, wA, 3 * DM, DM, 64, 64, CU_TENSOR_MAP_SWIZZLE_128B);
    make_map(enc, &mWA2, wA, 3 * DM, DM, 32, 64, CU_TENSOR_MAP_SWIZZLE_64B);
    make_map(enc, &mWB, wB, 3 * DM, DM, 64, 64, CU_TENSOR_MAP_SWIZZLE_128B);
    make_map(enc, &mWB2, wB, 3 * DM, DM, 32, 64, CU_TENSOR_MAP_SWIZZLE_64B);

    cudaStream_t stream = cudaStreamPerThread;
    cudaLaunchAttribute at[1];
    at[0].id = cudaLaunchAttributeProgrammaticStreamSerialization;
    at[0].val.programmaticStreamSerializationAllowed = 1;

    qkv_kernel<<<128, 256, K1_SMEM, stream>>>(mX, mWA, mWA2, mWB, mWB2);

    cudaLaunchConfig_t c2 = {};
    c2.gridDim = dim3(132); c2.blockDim = dim3(512); c2.dynamicSmemBytes = K2_SMEM; c2.stream = stream; c2.attrs = at; c2.numAttrs = 1;
    cudaLaunchKernelEx(&c2, attn_kernel, x, gw, woA, woB);

    cudaLaunchConfig_t c3 = {};
    c3.gridDim = dim3(96); c3.blockDim = dim3(288); c3.dynamicSmemBytes = K3_SMEM; c3.stream = stream; c3.attrs = at; c3.numAttrs = 1;
    cudaLaunchKernelEx(&c3, out_kernel, out);
}
```

```cpp
#include <cuda_runtime.h>
#include <cuda_bf16.h>
#include <cuda.h>
#include <stdint.h>

#define S_LEN 2048
#define DM 576
#define NH 32
#define DH 18
#define HEAD_ELEMS 49152
#define HEAD_BYTES 98304

#define POLY_BLK 0xAAAA

__device__ __align__(1024) __nv_bfloat16 g_T[6 * NH * HEAD_ELEMS];
__device__ float g_kmax[8][NH];
__device__ __align__(1024) __nv_bfloat16 g_O[2 * S_LEN * DM];
__device__ float g_gate[S_LEN];
__device__ __align__(128) __nv_bfloat16 g_kv[NH * 768];
__device__ int g_kvflag[NH];
__device__ __align__(1024) __nv_bfloat16 g_Wt[3 * 2 * 8 * 13824];

#define TSTAMP(k, i)
#define WG_FENCE() asm volatile("wgmma.fence.sync.aligned;\n" ::: "memory")
#define WG_COMMIT() asm volatile("wgmma.commit_group.sync.aligned;\n" ::: "memory")
#define WG_WAIT(n) asm volatile("wgmma.wait_group.sync.aligned %0;\n" :: "n"(n) : "memory")

__device__ __forceinline__ uint64_t mkdesc(uint32_t lo, uint32_t hi) {
    uint64_t d; asm("mov.b64 %0, {%1, %2};" : "=l"(d) : "r"(lo), "r"(hi)); return d;
}
__device__ __forceinline__ uint32_t smem_u32(const void* p) { return (uint32_t)__cvta_generic_to_shared(p); }
__device__ __forceinline__ void mbar_init(uint32_t bar, uint32_t cnt) { asm volatile("mbarrier.init.shared::cta.b64 [%0], %1;" :: "r"(bar), "r"(cnt)); }
__device__ __forceinline__ void mbar_expect_tx(uint32_t bar, uint32_t bytes) { asm volatile("mbarrier.arrive.expect_tx.shared::cta.b64 _, [%0], %1;" :: "r"(bar), "r"(bytes) : "memory"); }
__device__ __forceinline__ void mbar_arrive(uint32_t bar) { asm volatile("mbarrier.arrive.shared::cta.b64 _, [%0];" :: "r"(bar) : "memory"); }
__device__ __forceinline__ void mbar_wait(uint32_t bar, uint32_t parity) {
    asm volatile("{\n.reg .pred p;\nWAIT_%=:\nmbarrier.try_wait.parity.shared::cta.b64 p, [%0], %1;\n@p bra DONE_%=;\nbra WAIT_%=;\nDONE_%=:\n}\n" :: "r"(bar), "r"(parity) : "memory");
}
__device__ __forceinline__ void mbar_wait_w(uint32_t bar, uint32_t parity) { __syncwarp(); mbar_wait(bar, parity); }
__device__ __forceinline__ void bulk_g2s(uint32_t dst, const void* src, uint32_t bytes, uint32_t bar) {
    asm volatile("cp.async.bulk.shared::cluster.global.mbarrier::complete_tx::bytes [%0], [%1], %2, [%3];" :: "r"(dst), "l"(src), "r"(bytes), "r"(bar) : "memory");
}
__device__ __forceinline__ void tma_2d(uint32_t dst, const CUtensorMap* map, int c0, int c1, uint32_t bar) {
    asm volatile("cp.async.bulk.tensor.2d.shared::cluster.global.mbarrier::complete_tx::bytes [%0], [%1, {%3, %4}], [%2];"
                 :: "r"(dst), "l"((uint64_t)map), "r"(bar), "r"(c0), "r"(c1) : "memory");
}
__device__ __forceinline__ void cluster_arrive() { asm volatile("barrier.cluster.arrive.release.aligned;" ::: "memory"); }
__device__ __forceinline__ void cluster_wait() { asm volatile("barrier.cluster.wait.acquire.aligned;" ::: "memory"); }
__device__ __forceinline__ void named_bar(int id, int n) { asm volatile("bar.sync %0, %1;" :: "r"(id), "r"(n) : "memory"); }
__device__ __forceinline__ void fence_async() { asm volatile("fence.proxy.async.shared::cta;" ::: "memory"); }
__device__ __forceinline__ void pdl_wait() { asm volatile("griddepcontrol.wait;" ::: "memory"); }
__device__ __forceinline__ void pdl_launch() { asm volatile("griddepcontrol.launch_dependents;" ::: "memory"); }

__device__ __forceinline__ float ex2f(float x) { float y; asm("ex2.approx.ftz.f32 %0, %1;" : "=f"(y) : "f"(x)); return y; }
__device__ __forceinline__ uint32_t pack_bf16(float lo, float hi) { uint32_t r; asm("cvt.rn.bf16x2.f32 %0, %1, %2;" : "=r"(r) : "f"(hi), "f"(lo)); return r; }
__device__ __forceinline__ float bf_lo(uint32_t v) { return __uint_as_float(v << 16); }
__device__ __forceinline__ float bf_hi(uint32_t v) { return __uint_as_float(v & 0xFFFF0000u); }
__device__ __forceinline__ float bfr(float x) { return __uint_as_float(pack_bf16(0.f, x) & 0xFFFF0000u); }

#define ACC4(a, o) "+f"(a[o]), "+f"(a[o + 1]), "+f"(a[o + 2]), "+f"(a[o + 3])
#define ACC12(a, o) ACC4(a, o), ACC4(a, o + 4), ACC4(a, o + 8)
#define ACC16(a, o) ACC4(a, o), ACC4(a, o + 4), ACC4(a, o + 8), ACC4(a, o + 12)
#define ACC32(a, o) ACC16(a, o), ACC16(a, o + 16)

__device__ __forceinline__ void wgmma_n24_rs(float (&d)[12], uint32_t a0, uint32_t a1, uint32_t a2, uint32_t a3, uint64_t bdesc) {
    asm volatile("{\n.reg .pred p;\nsetp.ne.b32 p, 1, 0;\n"
        "wgmma.mma_async.sync.aligned.m64n24k16.f32.bf16.bf16 "
        "{%0,%1,%2,%3,%4,%5,%6,%7,%8,%9,%10,%11}, {%12,%13,%14,%15}, %16, p, 1, 1, 1;\n}\n"
        : ACC12(d, 0) : "r"(a0), "r"(a1), "r"(a2), "r"(a3), "l"(bdesc));
}
template<int TA, int TB>
__device__ __forceinline__ void wgmma_n24_ss(float (&d)[12], uint64_t adesc, uint64_t bdesc, int acc) {
    asm volatile("{\n.reg .pred p;\nsetp.ne.b32 p, %14, 0;\n"
        "wgmma.mma_async.sync.aligned.m64n24k16.f32.bf16.bf16 "
        "{%0,%1,%2,%3,%4,%5,%6,%7,%8,%9,%10,%11}, %12, %13, p, 1, 1, %15, %16;\n}\n"
        : ACC12(d, 0) : "l"(adesc), "l"(bdesc), "r"(acc), "n"(TA), "n"(TB));
}
template<int ACC>
__device__ __forceinline__ void wgmma_n128_rs(float (&d)[64], uint32_t a0, uint32_t a1, uint32_t a2, uint32_t a3, uint64_t bdesc) {
    asm volatile("{\n.reg .pred p;\nsetp.ne.b32 p, %69, 0;\n"
        "wgmma.mma_async.sync.aligned.m64n128k16.f32.bf16.bf16 "
        "{%0,%1,%2,%3,%4,%5,%6,%7,%8,%9,%10,%11,%12,%13,%14,%15,%16,%17,%18,%19,%20,%21,%22,%23,%24,%25,%26,%27,%28,%29,%30,%31,"
        "%32,%33,%34,%35,%36,%37,%38,%39,%40,%41,%42,%43,%44,%45,%46,%47,%48,%49,%50,%51,%52,%53,%54,%55,%56,%57,%58,%59,%60,%61,%62,%63}, {%64,%65,%66,%67}, %68, p, 1, 1, 0;\n}\n"
        : ACC32(d, 0), ACC32(d, 32) : "r"(a0), "r"(a1), "r"(a2), "r"(a3), "l"(bdesc), "n"(ACC));
}
__device__ __forceinline__ void wgmma_n192_ss(float (&d)[96], uint64_t adesc, uint64_t bdesc, int acc) {
    asm volatile("{\n.reg .pred p;\nsetp.ne.b32 p, %98, 0;\n"
        "wgmma.mma_async.sync.aligned.m64n192k16.f32.bf16.bf16 "
        "{%0,%1,%2,%3,%4,%5,%6,%7,%8,%9,%10,%11,%12,%13,%14,%15,%16,%17,%18,%19,%20,%21,%22,%23,%24,%25,%26,%27,%28,%29,%30,%31,"
        "%32,%33,%34,%35,%36,%37,%38,%39,%40,%41,%42,%43,%44,%45,%46,%47,%48,%49,%50,%51,%52,%53,%54,%55,%56,%57,%58,%59,%60,%61,%62,%63,"
        "%64,%65,%66,%67,%68,%69,%70,%71,%72,%73,%74,%75,%76,%77,%78,%79,%80,%81,%82,%83,%84,%85,%86,%87,%88,%89,%90,%91,%92,%93,%94,%95}, %96, %97, p, 1, 1, 0, 1;\n}\n"
        : ACC32(d, 0), ACC32(d, 32), ACC32(d, 64) : "l"(adesc), "l"(bdesc), "r"(acc));
}
template<int N> __device__ __forceinline__ void fence_regs(float (&d)[N]) {
    #pragma unroll
    for (int i = 0; i < N; i++) asm volatile("" : "+f"(d[i]) :: "memory");
}

#define K1_STAGES 3
#define K1_STAGE_BYTES 61440
#define K1_SMEM (K1_STAGES * K1_STAGE_BYTES + 1024)

__device__ __forceinline__ uint32_t hadd2_bf16(uint32_t a, uint32_t b) { uint32_t r; asm("add.rn.bf16x2 %0, %1, %2;" : "=r"(r) : "r"(a), "r"(b)); return r; }
__device__ __forceinline__ uint32_t phi_pair(uint32_t w) {
    const uint32_t p1 = hadd2_bf16(w, 0x3F803F80u);
    const uint32_t pe = pack_bf16(ex2f(bf_lo(w) * 1.4426950408889634f), ex2f(bf_hi(w) * 1.4426950408889634f));
    uint32_t m; asm("prmt.b32 %0, %1, 0, 0xBB99;" : "=r"(m) : "r"(w));
    const uint32_t r = (pe & m) | (p1 & ~m);
    return hadd2_bf16(r, 0x35863586u);
}
__device__ __forceinline__ void phi36(uint32_t (&w)[36]) {
    #pragma unroll
    for (int i = 0; i < 36; i++) w[i] = phi_pair(w[i]);
}
__device__ __forceinline__ uint32_t qscale_pair(uint32_t w) {
    const float qs = 0.23570226039551584f * 1.4426950408889634f;
    return pack_bf16(bf_lo(w) * qs, bf_hi(w) * qs);
}
__device__ __forceinline__ void sts32(uint32_t addr, uint32_t v) { asm volatile("st.shared.b32 [%0], %1;" :: "r"(addr), "r"(v) : "memory"); }

__global__ void __launch_bounds__(256, 1)
qkv_kernel(const __grid_constant__ CUtensorMap mapX, const __grid_constant__ CUtensorMap mapWA, const __grid_constant__ CUtensorMap mapWA2,
           const __grid_constant__ CUtensorMap mapWB, const __grid_constant__ CUtensorMap mapWB2) {
    extern __shared__ unsigned char smem_raw[];
    __shared__ __align__(8) uint64_t bars[2 * K1_STAGES];
    __shared__ uint32_t s_nmax[12];
    const uint32_t sbase = (smem_u32(smem_raw) + 1023u) & ~1023u;
    unsigned char* stg = smem_raw + (sbase - smem_u32(smem_raw));
    const uint32_t full0 = smem_u32(bars), empty0 = full0 + 8 * K1_STAGES;
    const int mt = blockIdx.x >> 4, nt = blockIdx.x & 15;
    const int branch = nt >> 3, n0 = (nt & 7) * 216, m0 = mt * 256;
    const int wg = threadIdx.x >> 7;
    const int warp = (threadIdx.x >> 5) & 3, lane = threadIdx.x & 31, g = lane >> 2, t = lane & 3;
    TSTAMP(0, 0);
    const CUtensorMap* w1 = branch ? &mapWB : &mapWA;
    const CUtensorMap* w2 = branch ? &mapWB2 : &mapWA2;
    auto issue = [&](int kt, int part) {
        const int s = kt % K1_STAGES;
        const uint32_t st = sbase + s * K1_STAGE_BYTES, fb = full0 + 8 * s;
        if (part == 0) {
            mbar_expect_tx(fb, K1_STAGE_BYTES);
            tma_2d(st, &mapX, kt * 64, m0, fb);
            tma_2d(st + 32768 + 24576, w2, n0 + 192, kt * 64, fb);
        } else {
            tma_2d(st + 32768, w1, n0, kt * 64, fb);
            tma_2d(st + 32768 + 8192, w1, n0 + 64, kt * 64, fb);
            tma_2d(st + 32768 + 16384, w1, n0 + 128, kt * 64, fb);
        }
    };
    if (threadIdx.x == 0) {
        for (int i = 0; i < K1_STAGES; i++) { mbar_init(full0 + 8 * i, 1); mbar_init(empty0 + 8 * i, 2); }
        asm volatile("fence.mbarrier_init.release.cluster;" ::: "memory");
        issue(0, 0); issue(0, 1);
    }
    if (threadIdx.x >= 64 && threadIdx.x < 76) s_nmax[threadIdx.x - 64] = 0;
    if (blockIdx.x == 0 && threadIdx.x >= 32 && threadIdx.x < 64) g_kvflag[threadIdx.x - 32] = 0;
    __syncthreads();
    if (lane == 0 && threadIdx.x < 128) issue(1 + (threadIdx.x >> 6), (threadIdx.x >> 5) & 1);
    pdl_launch();
    const uint32_t hiA = 64u | 0x40000000u;
    const uint32_t hiB = 64u | 0x40000000u;
    const uint32_t hiB2 = 32u | 0x80000000u;
    float acc0[96], acc1[96], acd0[12], acd1[12];
    #pragma unroll
    for (int i = 0; i < 96; i++) { acc0[i] = 0.f; acc1[i] = 0.f; }
    #pragma unroll
    for (int i = 0; i < 12; i++) { acd0[i] = 0.f; acd1[i] = 0.f; }
    fence_regs(acc0); fence_regs(acc1); fence_regs(acd0); fence_regs(acd1);
    #pragma unroll 1
    for (int kt = 0; kt < 9; kt++) {
        const int s = kt % K1_STAGES;
        mbar_wait_w(full0 + 8 * s, (kt / K1_STAGES) & 1);
        const uint32_t st = sbase + s * K1_STAGE_BYTES;
        const uint32_t a_lo = ((st + wg * 16384) >> 4) | (1u << 16);
        const uint32_t b_lo = ((st + 32768) >> 4) | (512u << 16);
        const uint32_t b2_lo = ((st + 32768 + 24576) >> 4) | (1u << 16);
        WG_FENCE();
        #pragma unroll
        for (int kk = 0; kk < 4; kk++) {
            wgmma_n192_ss(acc0, mkdesc(a_lo + kk * 2, hiA), mkdesc(b_lo + kk * 128, hiB), 1);
            wgmma_n24_ss<0, 1>(acd0, mkdesc(a_lo + kk * 2, hiA), mkdesc(b2_lo + kk * 64, hiB2), 1);
            wgmma_n192_ss(acc1, mkdesc(a_lo + 512 + kk * 2, hiA), mkdesc(b_lo + kk * 128, hiB), 1);
            wgmma_n24_ss<0, 1>(acd1, mkdesc(a_lo + 512 + kk * 2, hiA), mkdesc(b2_lo + kk * 64, hiB2), 1);
        }
        WG_COMMIT();
        WG_WAIT(1);
        if (kt > 0 && kt + 2 < 9) {
            const int sp = (kt - 1) % K1_STAGES;
            if ((threadIdx.x & 127) == 0) mbar_arrive(empty0 + 8 * sp);
            if (threadIdx.x < 32) {
                mbar_wait_w(empty0 + 8 * sp, ((kt - 1) / K1_STAGES) & 1);
                if (lane == 0) { issue(kt + 2, 0); issue(kt + 2, 1); }
            }
            __syncwarp();
        }
    }
    WG_WAIT(0);
    fence_regs(acc0); fence_regs(acc1); fence_regs(acd0); fence_regs(acd1);
    TSTAMP(0, 1);
    __syncthreads();
    {
        const int rgb = wg * 16 + warp * 2;
        const int k0 = branch * 3 + n0 / 576, k1 = branch * 3 + (n0 + 72) / 576, k2 = branch * 3 + (n0 + 144) / 576;
        const int row = threadIdx.x;
        if (k2 == 2) {
            const uint32_t pa = sbase + (row >> 3) * 384 + 256 + (row & 7) * 16 + 4;
            #pragma unroll
            for (int hh = 0; hh < 12; hh++) {
                if ((hh < 4 ? k0 : hh < 8 ? k1 : k2) == 2) {
                    sts32(pa + hh * 12288, 0x00003F80u);
                    asm volatile("st.shared.v2.b32 [%0], {%1, %1};" :: "r"(pa + hh * 12288 + 4), "r"(0u) : "memory");
                }
            }
        }
        auto flush = [&](int grp) {
            fence_async();
            __syncthreads();
            if (lane == 0 && threadIdx.x < 128) {
                const int hh = grp * 4 + (threadIdx.x >> 5), col0 = n0 + hh * 18;
                const int type = col0 / 576, head = (col0 % 576) / 18, kind = branch * 3 + type;
                const bool padded = kind == 1 || kind == 2;
                const size_t hb = padded ? (size_t)(NH + 2 * head) * HEAD_ELEMS + mt * 12288 + (kind - 1) * 6144
                                         : (size_t)(kind * NH + head) * HEAD_ELEMS + mt * 4608;
                asm volatile("cp.async.bulk.global.shared::cta.bulk_group [%0], [%1], %2;" :: "l"(g_T + hb), "r"(sbase + hh * 12288), "r"(padded ? 12288 : 9216) : "memory");
                asm volatile("cp.async.bulk.commit_group;" ::: "memory");
            }
            __syncwarp();
        };
        #pragma unroll
        for (int grp = 0; grp < 3; grp++) {
            uint32_t w[36];
            #pragma unroll
            for (int jj = 0; jj < 9; jj++) {
                const int j = grp * 9 + jj;
                if (j < 24) {
                    w[4 * jj] = pack_bf16(acc0[(4 * j) % 96], acc0[(4 * j + 1) % 96]); w[4 * jj + 1] = pack_bf16(acc0[(4 * j + 2) % 96], acc0[(4 * j + 3) % 96]);
                    w[4 * jj + 2] = pack_bf16(acc1[(4 * j) % 96], acc1[(4 * j + 1) % 96]); w[4 * jj + 3] = pack_bf16(acc1[(4 * j + 2) % 96], acc1[(4 * j + 3) % 96]);
                } else {
                    w[4 * jj] = pack_bf16(acd0[(4 * j) % 12], acd0[(4 * j + 1) % 12]); w[4 * jj + 1] = pack_bf16(acd0[(4 * j + 2) % 12], acd0[(4 * j + 3) % 12]);
                    w[4 * jj + 2] = pack_bf16(acd1[(4 * j) % 12], acd1[(4 * j + 1) % 12]); w[4 * jj + 3] = pack_bf16(acd1[(4 * j + 2) % 12], acd1[(4 * j + 3) % 12]);
                }
            }
            if (grp == 0 ? k0 == 1 : (grp == 2 && k2 == 1 && k1 != 1)) phi36(w);
            const int kg = grp == 0 ? k0 : grp == 1 ? k1 : k2;
            const bool padded = kg == 1 || kg == 2;
            const uint32_t cstride = padded ? 128u : 4096u, smain = padded ? 384u : 128u;
            const uint32_t bmain = sbase + grp * 49152 + rgb * smain + g * 16, btail = sbase + grp * 49152 + 8192 + (rgb * 8 + g) * 4;
            #pragma unroll
            for (int jj = 0; jj < 9; jj++) {
                const int c = 8 * jj + 2 * t, hh = c / 18, d = c - hh * 18;
                const bool tail = !padded && d == 16;
                const uint32_t a = hh * 12288 + (tail ? btail : bmain + (d >> 3) * cstride + (d & 7) * 2);
                const uint32_t s1 = tail ? 32u : smain;
                sts32(a, w[4 * jj]); sts32(a + s1, w[4 * jj + 1]); sts32(a + 8 * s1, w[4 * jj + 2]); sts32(a + 9 * s1, w[4 * jj + 3]);
            }
            flush(grp);
        }
        TSTAMP(0, 3);
        #pragma unroll 1
        for (int grp = 0; grp < 3; grp++) {
            if ((grp == 0 ? k0 : grp == 1 ? k1 : k2) == 4) {
                #pragma unroll 2
                for (int hq = 0; hq < 4; hq++) {
                    const unsigned char* src = stg + (grp * 4 + hq) * 12288;
                    const uint4 v0 = *(const uint4*)(src + row * 16), v1 = *(const uint4*)(src + 4096 + row * 16);
                    const uint32_t w[9] = {v0.x, v0.y, v0.z, v0.w, v1.x, v1.y, v1.z, v1.w, *(const uint32_t*)(src + 8192 + row * 4)};
                    float n2 = 0.f;
                    #pragma unroll
                    for (int i = 0; i < 9; i++) { const float a = bf_lo(w[i]), b = bf_hi(w[i]); n2 = fmaf(a, a, n2); n2 = fmaf(b, b, n2); }
                    uint32_t nb = __float_as_uint(n2);
                    if (!(n2 >= 0.f)) nb = 0x7F800000u;
                    nb = __reduce_max_sync(0xFFFFFFFFu, nb);
                    if (lane == 0) atomicMax(&s_nmax[grp * 4 + hq], nb);
                }
            }
        }
        __syncthreads();
        if (threadIdx.x < 12) {
            const int col0 = n0 + threadIdx.x * 18;
            if (branch == 1 && col0 / 576 == 1) g_kmax[mt][(col0 % 576) / 18] = __uint_as_float(s_nmax[threadIdx.x]);
        }
        if (lane == 0 && threadIdx.x < 128) asm volatile("cp.async.bulk.wait_group.read 0;" ::: "memory");
    }
    TSTAMP(0, 2);
}

__device__ __forceinline__ uint32_t hfma2(uint32_t a, uint32_t b, uint32_t c) { uint32_t r; asm("fma.rn.f16x2 %0, %1, %2, %3;" : "=r"(r) : "r"(a), "r"(b), "r"(c)); return r; }
__device__ __forceinline__ uint32_t and_or(uint32_t a, uint32_t m, uint32_t o) { uint32_t r; asm("lop3.b32 %0, %1, %2, %3, 0xEA;" : "=r"(r) : "r"(a), "r"(m), "r"(o)); return r; }
__device__ __forceinline__ uint32_t poly_ex2_pair(float t0, float t1) {
    const uint32_t u = __byte_perm(__float_as_uint(t0), __float_as_uint(t1), 0x5410);
    const uint32_t m = and_or(u, 0x03FF03FFu, 0x3C003C00u);
    uint32_t y = hfma2(m, 0x2CFE2CFEu, 0xA019A019u);
    y = hfma2(y, m, 0xB82EB82Eu);
    y = hfma2(y, m, 0x3FCF3FCFu);
    const uint32_t w = u + y + 0xC203C204u;
    return and_or(w >> 3, 0x1FFF1FFFu, 0x20002000u);
}

template<int B0, int NB>
__device__ __forceinline__ void softmax_blocks(float (&s)[64], uint32_t (&p)[32]) {
    #pragma unroll
    for (int i = B0 * 4; i < (B0 + NB) * 4; i++) asm volatile("" : "+f"(s[i]) :: "memory");
    #pragma unroll
    for (int b = B0; b < B0 + NB; b++) {
        if ((POLY_BLK >> b) & 1) {
            p[2 * b + 0] = poly_ex2_pair(s[4 * b], s[4 * b + 1]);
            p[2 * b + 1] = poly_ex2_pair(s[4 * b + 2], s[4 * b + 3]);
        } else {
            p[2 * b + 0] = pack_bf16(ex2f(s[4 * b]), ex2f(s[4 * b + 1]));
            p[2 * b + 1] = pack_bf16(ex2f(s[4 * b + 2]), ex2f(s[4 * b + 3]));
        }
    }
}

__device__ __forceinline__ void store_o(int branch, int row0, int h, int t, const float (&o)[12], float r0, float r1) {
    uint32_t* p = (uint32_t*)g_O + ((((branch * 16 + (row0 >> 7)) * 8 + (h >> 2)) * 16 + ((row0 >> 3) & 15)) * 72 + (row0 & 7)) * 4;
    uint32_t* q = p + (h & 3) * 64 + t;
    q[0] = pack_bf16(o[0] * r0, o[1] * r0); q[288] = pack_bf16(o[2] * r1, o[3] * r1);
    q[32] = pack_bf16(o[4] * r0, o[5] * r0); q[288 + 32] = pack_bf16(o[6] * r1, o[7] * r1);
    if (t == 0) { p[256 + (h & 3)] = pack_bf16(o[8] * r0, o[9] * r0); p[288 + 256 + (h & 3)] = pack_bf16(o[10] * r1, o[11] * r1); }
}

__device__ __forceinline__ void load_q(uint32_t (&q)[6], int h, int row0, int t) {
    const char* qb = (const char*)(g_T + (size_t)(3 * NH + h) * HEAD_ELEMS) + (row0 >> 8) * 9216;
    const uint32_t* q0 = (const uint32_t*)(qb + (row0 & 255) * 16) + t;
    q[0] = q0[0]; q[1] = q0[32]; q[2] = q0[1024]; q[3] = q0[1024 + 32];
    const uint32_t* qt = (const uint32_t*)(qb + 8192) + (row0 & 255);
    q[4] = t == 0 ? qt[0] : 0u; q[5] = t == 0 ? qt[8] : 0u;
}

#define K2_SMEM (2 * HEAD_BYTES + 24576 + 1536 + 1024)

__global__ void __launch_bounds__(512, 1)
attn_kernel(const __nv_bfloat16* __restrict__ x, const __nv_bfloat16* __restrict__ gate_w,
            const __nv_bfloat16* __restrict__ woA, const __nv_bfloat16* __restrict__ woB) {
    extern __shared__ unsigned char smem_raw[];
    __shared__ __align__(8) uint64_t bars[16];
    const uint32_t sK = (smem_u32(smem_raw) + 1023u) & ~1023u;
    const uint32_t sV = sK + HEAD_BYTES;
    unsigned char* sgen = smem_raw + (sK - smem_u32(smem_raw));
    TSTAMP(1, 0);
    const uint32_t bar0 = smem_u32(bars);
    const int wg = threadIdx.x >> 7, warp = (threadIdx.x >> 5) & 3, lane = threadIdx.x & 31, g = lane >> 2, t = lane & 3;
    if (threadIdx.x == 0) {
        for (int i = 0; i < 16; i++) mbar_init(bar0 + 8 * i, 1);
        asm volatile("fence.mbarrier_init.release.cluster;" ::: "memory");
    }
    __syncthreads();
    pdl_launch();
    const uint32_t kd0 = (sK >> 4) | (256u << 16);
    const uint32_t kd1 = ((sK + 8192) >> 4);
    const uint32_t khi = 8;
    const uint32_t vd0 = (sV >> 4) | (8u << 16);
    const uint32_t vhi = 256;
    const uint32_t phi8 = 8;

    if (blockIdx.x < 4) {
        const int w16 = blockIdx.x * 4 + wg;
        const int hd0 = w16 < 8 ? w16 : w16 < 12 ? w16 + 8 : w16 + 16, hd1 = w16 < 8 ? w16 + 8 : w16 + 12;
        const int tid = threadIdx.x & 127;
        {
            if (threadIdx.x < 8) asm volatile("cp.async.bulk.prefetch.L2.global [%0], %1;" :: "l"((const char*)((blockIdx.x & 1) ? woB : woA) + ((blockIdx.x >> 1) * 8 + threadIdx.x) * 41472), "r"(41472) : "memory");
            uint32_t gv[9];
            #pragma unroll
            for (int i = 0; i < 9; i++) gv[i] = ((const uint32_t*)gate_w)[lane + 32 * i];
            #pragma unroll 1
            for (int r = blockIdx.x * 512 + (threadIdx.x >> 5) * 8; r < blockIdx.x * 512 + 512; r += 128) {
                uint32_t xv[8][9];
                #pragma unroll
                for (int q = 0; q < 8; q++) {
                    #pragma unroll
                    for (int i = 0; i < 9; i++) xv[q][i] = ((const uint32_t*)(x + (size_t)(r + q) * DM))[lane + 32 * i];
                }
                float sum[8];
                #pragma unroll
                for (int q = 0; q < 8; q++) {
                    sum[q] = 0.f;
                    #pragma unroll
                    for (int i = 0; i < 9; i++) sum[q] += bfr(bf_lo(xv[q][i]) * bf_lo(gv[i])) + bfr(bf_hi(xv[q][i]) * bf_hi(gv[i]));
                }
                #pragma unroll
                for (int o = 16; o > 0; o >>= 1) {
                    #pragma unroll
                    for (int q = 0; q < 8; q++) sum[q] += __shfl_xor_sync(~0u, sum[q], o);
                }
                float z = sum[0];
                #pragma unroll
                for (int q = 1; q < 8; q++) z = lane == q ? sum[q] : z;
                if (lane < 8) g_gate[r + lane] = bfr(1.0f / (1.0f + __expf(-bfr(z))));
            }
        }
        TSTAMP(1, 3);
        pdl_wait();
        TSTAMP(1, 1);
        const uint32_t slot0 = sK + wg * 49152, fb0 = bar0 + wg * 16;
        auto issue = [&](int c) {
            mbar_expect_tx(fb0 + 8 * (c & 1), 24576);
            bulk_g2s(slot0 + (c & 1) * 24576, (const char*)(g_T + (size_t)(NH + 2 * (c < 8 ? hd0 : hd1)) * HEAD_ELEMS) + (size_t)(c & 7) * 24576, 24576, fb0 + 8 * (c & 1));
        };
        if (tid == 0) { issue(0); issue(1); }
        #pragma unroll 1
        for (int hi = 0; hi < 2; hi++) {
            float d1[4][12];
            #pragma unroll
            for (int k = 0; k < 4; k++) {
                #pragma unroll
                for (int i = 0; i < 12; i++) d1[k][i] = 0.f;
                fence_regs(d1[k]);
            }
            #pragma unroll 1
            for (int cc = 0; cc < 8; cc++) {
                const int c = hi * 8 + cc;
                mbar_wait_w(fb0 + 8 * (c & 1), (c >> 1) & 1);
                if (hi == 1) {
                    unsigned char* p = sgen + wg * 49152 + (c & 1) * 24576 + (tid >> 3) * 384 + (tid & 7) * 16;
                    uint4 v0 = *(uint4*)p, v1 = *(uint4*)(p + 128), v2 = *(uint4*)(p + 6144), v3 = *(uint4*)(p + 6144 + 128);
                    uint32_t w0 = *(uint32_t*)(p + 256), w1 = *(uint32_t*)(p + 6144 + 256);
                    v0.x = phi_pair(v0.x); v0.y = phi_pair(v0.y); v0.z = phi_pair(v0.z); v0.w = phi_pair(v0.w);
                    v1.x = phi_pair(v1.x); v1.y = phi_pair(v1.y); v1.z = phi_pair(v1.z); v1.w = phi_pair(v1.w);
                    v2.x = phi_pair(v2.x); v2.y = phi_pair(v2.y); v2.z = phi_pair(v2.z); v2.w = phi_pair(v2.w);
                    v3.x = phi_pair(v3.x); v3.y = phi_pair(v3.y); v3.z = phi_pair(v3.z); v3.w = phi_pair(v3.w);
                    *(uint4*)p = v0; *(uint4*)(p + 128) = v1; *(uint4*)(p + 6144) = v2; *(uint4*)(p + 6144 + 128) = v3;
                    *(uint32_t*)(p + 256) = phi_pair(w0); *(uint32_t*)(p + 6144 + 256) = phi_pair(w1);
                    fence_async();
                    named_bar(1 + wg, 128);
                }
                const uint32_t base = ((slot0 + (c & 1) * 24576) >> 4) | (24u << 16);
                WG_FENCE();
                #pragma unroll
                for (int ks = 0; ks < 16; ks++)
                    wgmma_n24_ss<1, 1>(d1[ks & 3], mkdesc(base + ks * 48, 8u), mkdesc(base + 768 + ks * 48, phi8), 1);
                WG_COMMIT();
                WG_WAIT(0);
                named_bar(1 + wg, 128);
                if (tid == 0 && c + 2 < 16) issue(c + 2);
            }
            #pragma unroll
            for (int k = 0; k < 4; k++) fence_regs(d1[k]);
            #pragma unroll
            for (int i = 0; i < 12; i++) d1[0][i] = (d1[0][i] + d1[1][i]) + (d1[2][i] + d1[3][i]);
            if (warp < 2) {
                const int d = warp * 16 + g;
                uint32_t* kp = (uint32_t*)(g_kv + (hi ? hd1 : hd0) * 768 + (d >> 3) * 192 + (d & 7) * 8 + 2 * t);
                #pragma unroll
                for (int j = 0; j < 3; j++) {
                    kp[32 * j] = d < 18 ? pack_bf16(d1[0][4 * j], d1[0][4 * j + 1]) : 0u;
                    kp[96 + 32 * j] = warp == 0 ? pack_bf16(d1[0][4 * j + 2], d1[0][4 * j + 3]) : 0u;
                }
                __threadfence();
            }
            named_bar(1 + wg, 128);
            if (tid == 0) asm volatile("st.release.gpu.global.b32 [%0], %1;" :: "l"(g_kvflag + (hi ? hd1 : hd0)), "r"(1) : "memory");
        }
        TSTAMP(1, 4);
        TSTAMP(1, 2);
        return;
    }
    const int cta = blockIdx.x - 4;

    {
        constexpr int PER = 82944 / 128, NQ = (PER + 511) / 512;
        uint4 wv[NQ];
        #pragma unroll
        for (int q = 0; q < NQ; q++) {
            const int id = cta * PER + threadIdx.x + q * 512;
            if (threadIdx.x + q * 512 < PER) wv[q] = *(const uint4*)((id >= 41472 ? woB - 41472 * 8 : woA) + (size_t)id * 8);
        }
        #pragma unroll
        for (int q = 0; q < NQ; q++) {
            const int id = cta * PER + threadIdx.x + q * 512;
            const int b = id >= 41472, r2 = id - b * 41472, k = r2 / 72, c = r2 % 72;
            const int hh = k / 18, d = k % 18;
            const int kp = (hh >> 2) * 72 + (d < 16 ? (hh & 3) * 16 + d : 64 + (hh & 3) * 2 + (d - 16));
            if (threadIdx.x + q * 512 < PER) *(uint4*)(g_Wt + ((((c / 24) * 2 + b) * 8 + kp / 72) * 24 + (c % 24)) * 576 + (kp % 72) * 8) = wv[q];
        }
    }

    const int h = cta >> 2, quarter = cta & 3;
    const uint32_t sPQ = sK + 2 * HEAD_BYTES, sKVt = sPQ + 24576;
    pdl_wait();
    TSTAMP(1, 1);
    auto issue_kv = [&](int c) {
        mbar_expect_tx(bar0 + 8 * c, 16384);
        bulk_g2s(sK + c * 12288, (const char*)(g_T + (size_t)(4 * NH + h) * HEAD_ELEMS) + c * 9216, 8192, bar0 + 8 * c);
        bulk_g2s(sV + c * 12288, (const char*)(g_T + (size_t)(5 * NH + h) * HEAD_ELEMS) + c * 9216, 8192, bar0 + 8 * c);
    };
    int kv_state = 0;
    auto kv_poll = [&](bool block) {
        if (threadIdx.x == 0 && kv_state != 2) {
            while (block && kv_state == 0) asm volatile("ld.acquire.gpu.global.b32 %0, [%1];" : "=r"(kv_state) : "l"(g_kvflag + h) : "memory");
            if (kv_state == 1) {
                asm volatile("fence.proxy.async.global;" ::: "memory");
                mbar_expect_tx(bar0 + 72, 1536);
                bulk_g2s(sKVt, g_kv + h * 768, 1536, bar0 + 72);
                kv_state = 2;
            } else {
                asm volatile("ld.acquire.gpu.global.b32 %0, [%1];" : "=r"(kv_state) : "l"(g_kvflag + h) : "memory");
            }
        }
    };
    float km2 = 0.f;
    #pragma unroll
    for (int i = 0; i < 8; i++) km2 = fmaxf(km2, g_kmax[i][h]);
    int s_fast_tmp = 0;
    uint32_t zr = 0u;
    asm volatile("" : "+r"(zr));
    uint32_t qf[2][6];
    #pragma unroll
    for (int pass = 0; pass < 2; pass++) {
        const int row0 = quarter * 512 + (wg * 2 + pass) * 64 + warp * 16 + g;
        load_q(qf[pass], h, row0, t);
    }
    uint32_t ktl[4], vtl[4];
    #pragma unroll
    for (int i = 0; i < 4; i++) {
        const int key = threadIdx.x + i * 512;
        ktl[i] = *(const uint32_t*)((const char*)(g_T + (size_t)(4 * NH + h) * HEAD_ELEMS) + (key >> 8) * 9216 + 8192 + (key & 255) * 4);
        vtl[i] = *(const uint32_t*)((const char*)(g_T + (size_t)(5 * NH + h) * HEAD_ELEMS) + (key >> 8) * 9216 + 8192 + (key & 255) * 4);
    }
    if (threadIdx.x == 0) issue_kv(0);
    if (threadIdx.x == 128) issue_kv(1);
    __syncwarp();
    #pragma unroll
    for (int i = 0; i < 6; i++) { qf[0][i] = qscale_pair(qf[0][i]); qf[1][i] = qscale_pair(qf[1][i]); }
    float mrow[2][2];
    bool ok = true;
    #pragma unroll
    for (int pass = 0; pass < 2; pass++) {
        auto sq = [](uint32_t v) { float a = bf_lo(v), b = bf_hi(v); return a * a + b * b; };
        float n0 = sq(qf[pass][0]) + sq(qf[pass][2]) + sq(qf[pass][4]);
        float n1 = sq(qf[pass][1]) + sq(qf[pass][3]) + sq(qf[pass][5]);
        n0 += __shfl_xor_sync(~0u, n0, 1); n0 += __shfl_xor_sync(~0u, n0, 2);
        n1 += __shfl_xor_sync(~0u, n1, 1); n1 += __shfl_xor_sync(~0u, n1, 2);
        mrow[pass][0] = sqrtf(n0 * km2) * 1.01f + 0.01f;
        mrow[pass][1] = sqrtf(n1 * km2) * 1.01f + 0.01f;
        ok = ok && (mrow[pass][0] <= 31.0f) && (mrow[pass][1] <= 31.0f);
    }
    #pragma unroll
    for (int i = 0; i < 4; i++) {
        const int key = threadIdx.x + i * 512;
        const uint32_t a = (key >> 8) * 12288 + 8192 + (key & 255) * 16;
        const uint32_t pmagic = ((POLY_BLK >> ((key & 127) >> 3)) & 1) ? 0x46013F80u : 0x3F803F80u;
        asm volatile("st.shared.v4.b32 [%0], {%1, %2, %3, %3};" :: "r"(sK + a), "r"(ktl[i]), "r"(pmagic), "r"(0u) : "memory");
        asm volatile("st.shared.v4.b32 [%0], {%1, %2, %3, %3};" :: "r"(sV + a), "r"(vtl[i]), "r"(0x00003F80u), "r"(0u) : "memory");
    }
    fence_async();
    __syncthreads();
    bool fast;
    asm volatile("{\n.reg .pred p, q;\nsetp.ne.b32 p, %1, 0;\nbar.red.and.pred q, %2, 128, p;\nselp.b32 %0, 1, 0, q;\n}\n"
                 : "=r"(*(int*)&s_fast_tmp) : "r"((int)ok), "r"(1 + wg) : "memory");
    fast = __all_sync(0xFFFFFFFFu, s_fast_tmp != 0);
    TSTAMP(1, 3);

    #pragma unroll 1
    for (int pass = 0; pass < 2; pass++) {
        const int row0 = quarter * 512 + (wg * 2 + pass) * 64 + warp * 16 + g;
        uint32_t qa[6];
        #pragma unroll
        for (int i = 0; i < 6; i++) qa[i] = pass ? qf[1][i] : qf[0][i];
        float o[12];
        #pragma unroll
        for (int i = 0; i < 12; i++) o[i] = 0.f;
        fence_regs(o);
        float s[64]; uint32_t p[32];
        #pragma unroll
        for (int i = 0; i < 64; i++) s[i] = 0.f;
        fence_regs(s);
        if (fast) {
            if (t == 1) { qa[4] = pack_bf16(-(pass ? mrow[1][0] : mrow[0][0]), 1.0f); qa[5] = pack_bf16(-(pass ? mrow[1][1] : mrow[0][1]), 1.0f); }
            #pragma unroll 1
            for (int j = 0; j < 16; j++) {
                if (pass == 0 && (j & 1) == 0) {
                    const int cn = (j >> 1) + 2;
                    if ((threadIdx.x & 127) == 0 && (cn & 3) == wg) {
                        if (cn < 8) issue_kv(cn);
                        else if (cn == 8) {
                            mbar_expect_tx(bar0 + 64, 16384);
                            bulk_g2s(sPQ, (const char*)(g_T + (size_t)h * HEAD_ELEMS) + quarter * 18432, 8192, bar0 + 64);
                            bulk_g2s(sPQ + 12288, (const char*)(g_T + (size_t)h * HEAD_ELEMS) + quarter * 18432 + 9216, 8192, bar0 + 64);
                        }
                    }
                    mbar_wait_w(bar0 + 8 * (j >> 1), 0);
                }
                const uint32_t ko = (j >> 1) * 768 + (j & 1) * 128;
                WG_FENCE();
                wgmma_n128_rs<0>(s, qa[0], qa[1], qa[2], qa[3], mkdesc(kd0 + ko, khi));
                wgmma_n128_rs<1>(s, qa[4], qa[5], zr, zr, mkdesc(kd1 + ko, khi));
                WG_COMMIT();
                if (pass == 1 && (j & 3) == 3) { kv_poll(false); __syncwarp(); }
                WG_WAIT(0);
                #pragma unroll
                for (int qd = 0; qd < 4; qd++) {
                    if (qd == 0) softmax_blocks<0, 4>(s, p);
                    if (qd == 1) softmax_blocks<4, 4>(s, p);
                    if (qd == 2) softmax_blocks<8, 4>(s, p);
                    if (qd == 3) softmax_blocks<12, 4>(s, p);
                    WG_FENCE();
                    wgmma_n24_rs(o, p[qd * 8 + 0], p[qd * 8 + 1], p[qd * 8 + 2], p[qd * 8 + 3], mkdesc(vd0 + ko + qd * 32, vhi));
                    wgmma_n24_rs(o, p[qd * 8 + 4], p[qd * 8 + 5], p[qd * 8 + 6], p[qd * 8 + 7], mkdesc(vd0 + ko + qd * 32 + 16, vhi));
                    WG_COMMIT();
                }
                WG_WAIT(0);
            }
        } else {
            {
                load_q(qa, h, row0, t);
            }
            const float qs = 0.23570226039551584f * 1.4426950408889634f;
            float mr0 = -INFINITY, mr1 = -INFINITY;
            #pragma unroll 1
            for (int j = 0; j < 16; j++) {
                if (pass == 0 && (j & 1) == 0) {
                    const int cn = (j >> 1) + 2;
                    if ((threadIdx.x & 127) == 0 && (cn & 3) == wg) {
                        if (cn < 8) issue_kv(cn);
                        else if (cn == 8) {
                            mbar_expect_tx(bar0 + 64, 16384);
                            bulk_g2s(sPQ, (const char*)(g_T + (size_t)h * HEAD_ELEMS) + quarter * 18432, 8192, bar0 + 64);
                            bulk_g2s(sPQ + 12288, (const char*)(g_T + (size_t)h * HEAD_ELEMS) + quarter * 18432 + 9216, 8192, bar0 + 64);
                        }
                    }
                    mbar_wait_w(bar0 + 8 * (j >> 1), 0);
                }
                const uint32_t ko = (j >> 1) * 768 + (j & 1) * 128;
                WG_FENCE();
                wgmma_n128_rs<0>(s, qa[0], qa[1], qa[2], qa[3], mkdesc(kd0 + ko, khi));
                wgmma_n128_rs<1>(s, qa[4], qa[5], zr, zr, mkdesc(kd1 + ko, khi));
                WG_COMMIT();
                WG_WAIT(0);
                fence_regs(s); fence_regs(o);
                float x0 = mr0, x1 = mr1;
                #pragma unroll
                for (int b = 0; b < 16; b++) {
                    x0 = fmaxf(x0, fmaxf(s[4 * b], s[4 * b + 1]));
                    x1 = fmaxf(x1, fmaxf(s[4 * b + 2], s[4 * b + 3]));
                }
                x0 = fmaxf(x0, __shfl_xor_sync(~0u, x0, 1)); x0 = fmaxf(x0, __shfl_xor_sync(~0u, x0, 2));
                x1 = fmaxf(x1, __shfl_xor_sync(~0u, x1, 1)); x1 = fmaxf(x1, __shfl_xor_sync(~0u, x1, 2));
                const float c0 = exp2f((mr0 - x0) * qs), c1 = exp2f((mr1 - x1) * qs);
                mr0 = x0; mr1 = x1;
                #pragma unroll
                for (int i = 0; i < 12; i++) o[i] *= (i & 2) ? c1 : c0;
                #pragma unroll
                for (int b = 0; b < 16; b++) {
                    p[2 * b] = pack_bf16(exp2f((s[4 * b] - x0) * qs), exp2f((s[4 * b + 1] - x0) * qs));
                    p[2 * b + 1] = pack_bf16(exp2f((s[4 * b + 2] - x1) * qs), exp2f((s[4 * b + 3] - x1) * qs));
                }
                fence_regs(o);
                WG_FENCE();
                #pragma unroll
                for (int kk = 0; kk < 8; kk++)
                    wgmma_n24_rs(o, p[kk * 4 + 0], p[kk * 4 + 1], p[kk * 4 + 2], p[kk * 4 + 3], mkdesc(vd0 + ko + kk * 16, vhi));
                WG_COMMIT();
                WG_WAIT(0);
            }
        }
        fence_regs(o);
        const float l0 = __shfl_sync(~0u, o[8], (lane & ~3) | 1);
        const float l1 = __shfl_sync(~0u, o[10], (lane & ~3) | 1);
        store_o(1, row0, h, t, o, 1.0f / l0, 1.0f / l1);
    }
    TSTAMP(1, 4);
    {
        const uint32_t qtl = *(const uint32_t*)((const char*)(g_T + (size_t)h * HEAD_ELEMS) + (quarter * 2 + (wg >> 1)) * 9216 + 8192 + ((wg & 1) * 128 + (threadIdx.x & 127)) * 4);
        kv_poll(true); kv_poll(true);
        mbar_wait_w(bar0 + 64, 0);
        {
            const int tid = threadIdx.x & 127, r = (wg & 1) * 128 + tid;
            unsigned char* pq = sgen + 2 * HEAD_BYTES + (wg >> 1) * 12288 + r * 16;
            uint4 v0 = *(uint4*)pq, v1 = *(uint4*)(pq + 4096);
            v0.x = phi_pair(v0.x); v0.y = phi_pair(v0.y); v0.z = phi_pair(v0.z); v0.w = phi_pair(v0.w);
            v1.x = phi_pair(v1.x); v1.y = phi_pair(v1.y); v1.z = phi_pair(v1.z); v1.w = phi_pair(v1.w);
            *(uint4*)pq = v0; *(uint4*)(pq + 4096) = v1;
            *(uint4*)(pq + 8192) = make_uint4(phi_pair(qtl), 0u, 0u, 0u);
            fence_async();
        }
        named_bar(1 + wg, 128);
        mbar_wait_w(bar0 + 72, 0);
        float e[4][12];
        #pragma unroll
        for (int k = 0; k < 4; k++) {
            #pragma unroll
            for (int i = 0; i < 12; i++) e[k][i] = 0.f;
            fence_regs(e[k]);
        }
        const uint32_t ab = (sPQ + (wg >> 1) * 12288 + (wg & 1) * 2048) >> 4, bb = (sKVt >> 4) | (24u << 16);
        WG_FENCE();
        wgmma_n24_ss<0, 1>(e[0], mkdesc(ab | (256u << 16), khi), mkdesc(bb, phi8), 0);
        wgmma_n24_ss<0, 1>(e[1], mkdesc((ab + 64) | (256u << 16), khi), mkdesc(bb, phi8), 0);
        wgmma_n24_ss<0, 1>(e[2], mkdesc(ab + 512, khi), mkdesc(bb + 48, phi8), 0);
        wgmma_n24_ss<0, 1>(e[3], mkdesc(ab + 64 + 512, khi), mkdesc(bb + 48, phi8), 0);
        WG_COMMIT();
        WG_WAIT(0);
        #pragma unroll
        for (int k = 0; k < 4; k++) fence_regs(e[k]);
        #pragma unroll
        for (int m = 0; m < 2; m++) {
            #pragma unroll
            for (int i = 0; i < 12; i++) e[m][i] = bfr(e[m][i] + e[m + 2][i]);
            const float l0 = __shfl_sync(~0u, e[m][8], (lane & ~3) | 1), l1 = __shfl_sync(~0u, e[m][10], (lane & ~3) | 1);
            store_o(0, quarter * 512 + (wg * 2 + m) * 64 + warp * 16 + g, h, t, e[m], 1.0f / bfr(l0 + 1e-6f), 1.0f / bfr(l1 + 1e-6f));
        }
    }
    TSTAMP(1, 2);
}

#define K3_UNITS 4
#define K3_UNIT_BYTES 46080
#define K3_SMEM (K3_UNITS * K3_UNIT_BYTES + 26624 + 1024)

__global__ void __cluster_dims__(2, 1, 1) __launch_bounds__(288, 1)
out_kernel(__nv_bfloat16* __restrict__ out) {
    extern __shared__ unsigned char smem_raw[];
    __shared__ __align__(8) uint64_t bars[2 * K3_UNITS + 8];
    const uint32_t sA = (smem_u32(smem_raw) + 1023u) & ~1023u;
    const uint32_t sX = sA + K3_UNITS * K3_UNIT_BYTES;
    const uint32_t full0 = smem_u32(bars), empty0 = full0 + 8 * K3_UNITS;
    const int br = blockIdx.x & 1, tile = blockIdx.x >> 1, mt = tile / 3, nt = tile % 3;
    const int m0 = mt * 128, n0 = nt * 192;
    TSTAMP(2, 0);
    if (threadIdx.x == 0) {
        for (int i = 0; i < K3_UNITS; i++) { mbar_init(full0 + 8 * i, 1); mbar_init(empty0 + 8 * i, 2); }
        for (int i = 0; i < 8; i++) mbar_init(full0 + 16 * K3_UNITS + 8 * i, 1);
        asm volatile("fence.mbarrier_init.release.cluster;" ::: "memory");
    }
    __syncthreads();
    cluster_arrive();
    TSTAMP(2, 3);
    pdl_wait();
    TSTAMP(2, 1);
    const int wg = threadIdx.x >> 7;
    if (wg == 2) {
        if (threadIdx.x == 256) {
            for (int c = 0; c < 8; c++) {
                const int s = c % K3_UNITS;
                if (c >= K3_UNITS) mbar_wait(empty0 + 8 * s, 0);
                const uint32_t st = sA + s * K3_UNIT_BYTES;
                mbar_expect_tx(full0 + 8 * s, K3_UNIT_BYTES);
                bulk_g2s(st, g_O + (size_t)((br * 16 + mt) * 8 + c) * 9216, 18432, full0 + 8 * s);
                bulk_g2s(st + 18432, g_Wt + (size_t)((nt * 2 + br) * 8 + c) * 13824, 27648, full0 + 8 * s);
            }
        }
        __syncwarp();
        cluster_wait();
        cluster_arrive();
    } else {
        const int warp = (threadIdx.x >> 5) & 3, lane = threadIdx.x & 31, g = lane >> 2, t = lane & 3;
        float acc[96];
        #pragma unroll
        for (int i = 0; i < 96; i++) acc[i] = 0.f;
        fence_regs(acc);
        const uint32_t hiA = 72u;
        const uint32_t hiB = 72u;
        const int r0 = m0 + wg * 64 + warp * 16 + g;
        float g0 = g_gate[r0], g1 = g_gate[r0 + 8];
        if (br) { g0 = bfr(1.0f - g0); g1 = bfr(1.0f - g1); }
        #pragma unroll 1
        for (int pr = 0; pr < 4; pr++) {
            const int s = (pr & 1) * 2;
            const uint32_t a_lo = ((sA + s * K3_UNIT_BYTES + wg * 9216) & 0x3FFFF) >> 4;
            const uint32_t b_lo = ((sA + s * K3_UNIT_BYTES + 18432) & 0x3FFFF) >> 4;
            mbar_wait_w(full0 + 8 * s, pr >> 1);
            if (pr == 0) TSTAMP(2, 4);
            WG_FENCE();
            #pragma unroll
            for (int i = 0; i < 4; i++) wgmma_n192_ss(acc, mkdesc((a_lo + i * 16) | (8u << 16), hiA), mkdesc((b_lo + i * 16) | (8u << 16), hiB), 1);
            WG_COMMIT();
            mbar_wait_w(full0 + 8 * s + 8, pr >> 1);
            WG_FENCE();
            wgmma_n192_ss(acc, mkdesc((a_lo + 64) | ((K3_UNIT_BYTES / 16 - 64) << 16), hiA), mkdesc((b_lo + 64) | ((K3_UNIT_BYTES / 16 - 64) << 16), hiB), 1);
            #pragma unroll
            for (int i = 0; i < 4; i++)
                wgmma_n192_ss(acc, mkdesc((a_lo + K3_UNIT_BYTES / 16 + 8 + i * 16) | (8u << 16), hiA), mkdesc((b_lo + K3_UNIT_BYTES / 16 + 8 + i * 16) | (8u << 16), hiB), 1);
            WG_COMMIT();
            if (pr < 2) {
                WG_WAIT(0);
                if ((threadIdx.x & 127) < 2) mbar_arrive(empty0 + 8 * (s + (threadIdx.x & 1)));
            }
        }
        WG_WAIT(0);
        fence_regs(acc);
        TSTAMP(2, 5);
        uint32_t keep[24];
        named_bar(1, 256);
        const uint32_t snd = sA + (wg * 4 + warp) * 3328;
        #pragma unroll
        for (int j = 0; j < 24; j++) {
            const uint32_t v0 = pack_bf16(g0 * bfr(acc[4 * j]), g0 * bfr(acc[4 * j + 1]));
            const uint32_t v1 = pack_bf16(g1 * bfr(acc[4 * j + 2]), g1 * bfr(acc[4 * j + 3]));
            const int jj = j % 12;
            if ((j < 12) == (br == 0)) { keep[2 * jj] = v0; keep[2 * jj + 1] = v1; }
            else { sts32(snd + g * 208 + jj * 16 + t * 4, v0); sts32(snd + (g + 8) * 208 + jj * 16 + t * 4, v1); }
        }
        fence_async();
        __syncwarp();
        cluster_wait();
        const uint32_t xbar = full0 + 16 * K3_UNITS + 8 * (wg * 4 + warp);
        if (lane == 0) {
            uint32_t rdst, rbar;
            asm volatile("mapa.shared::cluster.u32 %0, %1, %2;" : "=r"(rdst) : "r"(sX + (wg * 4 + warp) * 3328), "r"(br ^ 1));
            asm volatile("mapa.shared::cluster.u32 %0, %1, %2;" : "=r"(rbar) : "r"(xbar), "r"(br ^ 1));
            mbar_expect_tx(xbar, 3328);
            asm volatile("cp.async.bulk.shared::cluster.shared::cta.mbarrier::complete_tx::bytes [%0], [%1], %2, [%3];"
                         :: "r"(rdst), "r"(snd), "r"(3328), "r"(rbar) : "memory");
        }
        mbar_wait_w(xbar, 0);
        cluster_arrive();
        const uint32_t sx = sX + (wg * 64 + warp * 16) * 208;
        #pragma unroll
        for (int jj = 0; jj < 12; jj++) {
            uint32_t p0, p1;
            asm volatile("ld.shared.b32 %0, [%1];" : "=r"(p0) : "r"(sx + g * 208 + jj * 16 + t * 4));
            asm volatile("ld.shared.b32 %0, [%1];" : "=r"(p1) : "r"(sx + (g + 8) * 208 + jj * 16 + t * 4));
            sts32(sx + g * 208 + jj * 16 + t * 4, hadd2_bf16(keep[2 * jj], p0));
            sts32(sx + (g + 8) * 208 + jj * 16 + t * 4, hadd2_bf16(keep[2 * jj + 1], p1));
        }
        __syncwarp();
        #pragma unroll
        for (int i = 0; i < 6; i++) {
            const int id = i * 32 + lane, r = id / 12, c = id % 12;
            uint4 v;
            asm volatile("ld.shared.v4.b32 {%0,%1,%2,%3}, [%4];" : "=r"(v.x), "=r"(v.y), "=r"(v.z), "=r"(v.w) : "r"(sx + r * 208 + c * 16));
            *(uint4*)(out + (size_t)(m0 + wg * 64 + warp * 16 + r) * DM + n0 + br * 96 + c * 8) = v;
        }
        TSTAMP(2, 2);
    }
    cluster_wait();
}

typedef CUresult (*EncodeFn)(CUtensorMap*, CUtensorMapDataType, cuuint32_t, void*, const cuuint64_t*, const cuuint64_t*,
                             const cuuint32_t*, const cuuint32_t*, CUtensorMapInterleave, CUtensorMapSwizzle,
                             CUtensorMapL2promotion, CUtensorMapFloatOOBfill);

static void make_map(EncodeFn enc, CUtensorMap* m, const void* base, uint64_t inner, uint64_t outer, uint32_t box_in, uint32_t box_out, CUtensorMapSwizzle sw) {
    cuuint64_t dims[2] = {inner, outer};
    cuuint64_t strides[1] = {inner * 2};
    cuuint32_t box[2] = {box_in, box_out};
    cuuint32_t es[2] = {1, 1};
    enc(m, CU_TENSOR_MAP_DATA_TYPE_BFLOAT16, 2, (void*)base, dims, strides, box, es, CU_TENSOR_MAP_INTERLEAVE_NONE, sw,
        CU_TENSOR_MAP_L2_PROMOTION_L2_256B, CU_TENSOR_MAP_FLOAT_OOB_FILL_NONE);
}

extern "C" void kernel_launch(void* const* d_in, const int* in_sizes, int n_in, void* d_out, int out_size) {
    const __nv_bfloat16* x = (const __nv_bfloat16*)d_in[0];
    const __nv_bfloat16* wA = (const __nv_bfloat16*)d_in[1];
    const __nv_bfloat16* woA = (const __nv_bfloat16*)d_in[2];
    const __nv_bfloat16* wB = (const __nv_bfloat16*)d_in[4];
    const __nv_bfloat16* woB = (const __nv_bfloat16*)d_in[5];
    const __nv_bfloat16* gw = (const __nv_bfloat16*)d_in[6];
    __nv_bfloat16* out = (__nv_bfloat16*)d_out;

    static EncodeFn enc = nullptr;
    if (!enc) {
        void* fn = nullptr; cudaDriverEntryPointQueryResult st;
        cudaGetDriverEntryPoint("cuTensorMapEncodeTiled", &fn, cudaEnableDefault, &st);
        enc = (EncodeFn)fn;
        cudaFuncSetAttribute(qkv_kernel, cudaFuncAttributeMaxDynamicSharedMemorySize, K1_SMEM);
        cudaFuncSetAttribute(attn_kernel, cudaFuncAttributeMaxDynamicSharedMemorySize, K2_SMEM);
        cudaFuncSetAttribute(out_kernel, cudaFuncAttributeMaxDynamicSharedMemorySize, K3_SMEM);
    }
    CUtensorMap mX, mWA, mWA2, mWB, mWB2;
    make_map(enc, &mX, x, DM, S_LEN, 64, 256, CU_TENSOR_MAP_SWIZZLE_128B);
    make_map(enc, &mWA, wA, 3 * DM, DM, 64, 64, CU_TENSOR_MAP_SWIZZLE_128B);
    make_map(enc, &mWA2, wA, 3 * DM, DM, 32, 64, CU_TENSOR_MAP_SWIZZLE_64B);
    make_map(enc, &mWB, wB, 3 * DM, DM, 64, 64, CU_TENSOR_MAP_SWIZZLE_128B);
    make_map(enc, &mWB2, wB, 3 * DM, DM, 32, 64, CU_TENSOR_MAP_SWIZZLE_64B);

    cudaStream_t stream = cudaStreamPerThread;
    cudaLaunchAttribute at[1];
    at[0].id = cudaLaunchAttributeProgrammaticStreamSerialization;
    at[0].val.programmaticStreamSerializationAllowed = 1;

    qkv_kernel<<<128, 256, K1_SMEM, stream>>>(mX, mWA, mWA2, mWB, mWB2);

    cudaLaunchConfig_t c2 = {};
    c2.gridDim = dim3(132); c2.blockDim = dim3(512); c2.dynamicSmemBytes = K2_SMEM; c2.stream = stream; c2.attrs = at; c2.numAttrs = 1;
    cudaLaunchKernelEx(&c2, attn_kernel, x, gw, woA, woB);

    cudaLaunchConfig_t c3 = {};
    c3.gridDim = dim3(96); c3.blockDim = dim3(288); c3.dynamicSmemBytes = K3_SMEM; c3.stream = stream; c3.attrs = at; c3.numAttrs = 1;
    cudaLaunchKernelEx(&c3, out_kernel, out);
}
```

```cpp
#include <cuda_runtime.h>
#include <cuda_bf16.h>
#include <cuda.h>
#include <stdint.h>

#define S_LEN 2048
#define DM 576
#define NH 32
#define DH 18
#define HEAD_ELEMS 49152
#define HEAD_BYTES 98304

#define POLY_BLK 0xAAAA

__device__ __align__(1024) __nv_bfloat16 g_T[6 * NH * HEAD_ELEMS];
__device__ float g_kmax[8][NH];
__device__ __align__(1024) __nv_bfloat16 g_O[2 * S_LEN * DM];
__device__ float g_gate[S_LEN];
__device__ __align__(128) __nv_bfloat16 g_kv[NH * 768];
__device__ int g_kvflag[NH];
__device__ __align__(1024) __nv_bfloat16 g_Wt[3 * 2 * 8 * 13824];

#define TSTAMP(k, i)
#define WG_FENCE() asm volatile("wgmma.fence.sync.aligned;\n" ::: "memory")
#define WG_COMMIT() asm volatile("wgmma.commit_group.sync.aligned;\n" ::: "memory")
#define WG_WAIT(n) asm volatile("wgmma.wait_group.sync.aligned %0;\n" :: "n"(n) : "memory")

__device__ __forceinline__ uint64_t mkdesc(uint32_t lo, uint32_t hi) {
    uint64_t d; asm("mov.b64 %0, {%1, %2};" : "=l"(d) : "r"(lo), "r"(hi)); return d;
}
__device__ __forceinline__ uint32_t smem_u32(const void* p) { return (uint32_t)__cvta_generic_to_shared(p); }
__device__ __forceinline__ void mbar_init(uint32_t bar, uint32_t cnt) { asm volatile("mbarrier.init.shared::cta.b64 [%0], %1;" :: "r"(bar), "r"(cnt)); }
__device__ __forceinline__ void mbar_expect_tx(uint32_t bar, uint32_t bytes) { asm volatile("mbarrier.arrive.expect_tx.shared::cta.b64 _, [%0], %1;" :: "r"(bar), "r"(bytes) : "memory"); }
__device__ __forceinline__ void mbar_arrive(uint32_t bar) { asm volatile("mbarrier.arrive.shared::cta.b64 _, [%0];" :: "r"(bar) : "memory"); }
__device__ __forceinline__ void mbar_wait(uint32_t bar, uint32_t parity) {
    asm volatile("{\n.reg .pred p;\nWAIT_%=:\nmbarrier.try_wait.parity.shared::cta.b64 p, [%0], %1;\n@p bra DONE_%=;\nbra WAIT_%=;\nDONE_%=:\n}\n" :: "r"(bar), "r"(parity) : "memory");
}
__device__ __forceinline__ void mbar_wait_w(uint32_t bar, uint32_t parity) { __syncwarp(); mbar_wait(bar, parity); }
__device__ __forceinline__ void bulk_g2s(uint32_t dst, const void* src, uint32_t bytes, uint32_t bar) {
    asm volatile("cp.async.bulk.shared::cluster.global.mbarrier::complete_tx::bytes [%0], [%1], %2, [%3];" :: "r"(dst), "l"(src), "r"(bytes), "r"(bar) : "memory");
}
__device__ __forceinline__ void tma_2d(uint32_t dst, const CUtensorMap* map, int c0, int c1, uint32_t bar) {
    asm volatile("cp.async.bulk.tensor.2d.shared::cluster.global.mbarrier::complete_tx::bytes [%0], [%1, {%3, %4}], [%2];"
                 :: "r"(dst), "l"((uint64_t)map), "r"(bar), "r"(c0), "r"(c1) : "memory");
}
__device__ __forceinline__ void cluster_arrive() { asm volatile("barrier.cluster.arrive.release.aligned;" ::: "memory"); }
__device__ __forceinline__ void cluster_wait() { asm volatile("barrier.cluster.wait.acquire.aligned;" ::: "memory"); }
__device__ __forceinline__ void named_bar(int id, int n) { asm volatile("bar.sync %0, %1;" :: "r"(id), "r"(n) : "memory"); }
__device__ __forceinline__ void fence_async() { asm volatile("fence.proxy.async.shared::cta;" ::: "memory"); }
__device__ __forceinline__ void pdl_wait() { asm volatile("griddepcontrol.wait;" ::: "memory"); }
__device__ __forceinline__ void pdl_launch() { asm volatile("griddepcontrol.launch_dependents;" ::: "memory"); }

__device__ __forceinline__ float ex2f(float x) { float y; asm("ex2.approx.ftz.f32 %0, %1;" : "=f"(y) : "f"(x)); return y; }
__device__ __forceinline__ uint32_t pack_bf16(float lo, float hi) { uint32_t r; asm("cvt.rn.bf16x2.f32 %0, %1, %2;" : "=r"(r) : "f"(hi), "f"(lo)); return r; }
__device__ __forceinline__ float bf_lo(uint32_t v) { return __uint_as_float(v << 16); }
__device__ __forceinline__ float bf_hi(uint32_t v) { return __uint_as_float(v & 0xFFFF0000u); }
__device__ __forceinline__ float bfr(float x) { return __uint_as_float(pack_bf16(0.f, x) & 0xFFFF0000u); }

#define ACC4(a, o) "+f"(a[o]), "+f"(a[o + 1]), "+f"(a[o + 2]), "+f"(a[o + 3])
#define ACC12(a, o) ACC4(a, o), ACC4(a, o + 4), ACC4(a, o + 8)
#define ACC16(a, o) ACC4(a, o), ACC4(a, o + 4), ACC4(a, o + 8), ACC4(a, o + 12)
#define ACC32(a, o) ACC16(a, o), ACC16(a, o + 16)

__device__ __forceinline__ void wgmma_n24_rs(float (&d)[12], uint32_t a0, uint32_t a1, uint32_t a2, uint32_t a3, uint64_t bdesc) {
    asm volatile("{\n.reg .pred p;\nsetp.ne.b32 p, 1, 0;\n"
        "wgmma.mma_async.sync.aligned.m64n24k16.f32.bf16.bf16 "
        "{%0,%1,%2,%3,%4,%5,%6,%7,%8,%9,%10,%11}, {%12,%13,%14,%15}, %16, p, 1, 1, 1;\n}\n"
        : ACC12(d, 0) : "r"(a0), "r"(a1), "r"(a2), "r"(a3), "l"(bdesc));
}
template<int TA, int TB>
__device__ __forceinline__ void wgmma_n24_ss(float (&d)[12], uint64_t adesc, uint64_t bdesc, int acc) {
    asm volatile("{\n.reg .pred p;\nsetp.ne.b32 p, %14, 0;\n"
        "wgmma.mma_async.sync.aligned.m64n24k16.f32.bf16.bf16 "
        "{%0,%1,%2,%3,%4,%5,%6,%7,%8,%9,%10,%11}, %12, %13, p, 1, 1, %15, %16;\n}\n"
        : ACC12(d, 0) : "l"(adesc), "l"(bdesc), "r"(acc), "n"(TA), "n"(TB));
}
template<int ACC>
__device__ __forceinline__ void wgmma_n128_rs(float (&d)[64], uint32_t a0, uint32_t a1, uint32_t a2, uint32_t a3, uint64_t bdesc) {
    asm volatile("{\n.reg .pred p;\nsetp.ne.b32 p, %69, 0;\n"
        "wgmma.mma_async.sync.aligned.m64n128k16.f32.bf16.bf16 "
        "{%0,%1,%2,%3,%4,%5,%6,%7,%8,%9,%10,%11,%12,%13,%14,%15,%16,%17,%18,%19,%20,%21,%22,%23,%24,%25,%26,%27,%28,%29,%30,%31,"
        "%32,%33,%34,%35,%36,%37,%38,%39,%40,%41,%42,%43,%44,%45,%46,%47,%48,%49,%50,%51,%52,%53,%54,%55,%56,%57,%58,%59,%60,%61,%62,%63}, {%64,%65,%66,%67}, %68, p, 1, 1, 0;\n}\n"
        : ACC32(d, 0), ACC32(d, 32) : "r"(a0), "r"(a1), "r"(a2), "r"(a3), "l"(bdesc), "n"(ACC));
}
__device__ __forceinline__ void wgmma_n192_ss(float (&d)[96], uint64_t adesc, uint64_t bdesc, int acc) {
    asm volatile("{\n.reg .pred p;\nsetp.ne.b32 p, %98, 0;\n"
        "wgmma.mma_async.sync.aligned.m64n192k16.f32.bf16.bf16 "
        "{%0,%1,%2,%3,%4,%5,%6,%7,%8,%9,%10,%11,%12,%13,%14,%15,%16,%17,%18,%19,%20,%21,%22,%23,%24,%25,%26,%27,%28,%29,%30,%31,"
        "%32,%33,%34,%35,%36,%37,%38,%39,%40,%41,%42,%43,%44,%45,%46,%47,%48,%49,%50,%51,%52,%53,%54,%55,%56,%57,%58,%59,%60,%61,%62,%63,"
        "%64,%65,%66,%67,%68,%69,%70,%71,%72,%73,%74,%75,%76,%77,%78,%79,%80,%81,%82,%83,%84,%85,%86,%87,%88,%89,%90,%91,%92,%93,%94,%95}, %96, %97, p, 1, 1, 0, 1;\n}\n"
        : ACC32(d, 0), ACC32(d, 32), ACC32(d, 64) : "l"(adesc), "l"(bdesc), "r"(acc));
}
template<int N> __device__ __forceinline__ void fence_regs(float (&d)[N]) {
    #pragma unroll
    for (int i = 0; i < N; i++) asm volatile("" : "+f"(d[i]) :: "memory");
}

#define K1_STAGES 3
#define K1_STAGE_BYTES 61440
#define K1_SMEM (K1_STAGES * K1_STAGE_BYTES + 1024)

__device__ __forceinline__ uint32_t hadd2_bf16(uint32_t a, uint32_t b) { uint32_t r; asm("add.rn.bf16x2 %0, %1, %2;" : "=r"(r) : "r"(a), "r"(b)); return r; }
__device__ __forceinline__ uint32_t phi_pair(uint32_t w) {
    const uint32_t p1 = hadd2_bf16(w, 0x3F803F80u);
    const uint32_t pe = pack_bf16(ex2f(bf_lo(w) * 1.4426950408889634f), ex2f(bf_hi(w) * 1.4426950408889634f));
    uint32_t m; asm("prmt.b32 %0, %1, 0, 0xBB99;" : "=r"(m) : "r"(w));
    const uint32_t r = (pe & m) | (p1 & ~m);
    return hadd2_bf16(r, 0x35863586u);
}
__device__ __forceinline__ void phi36(uint32_t (&w)[36]) {
    #pragma unroll
    for (int i = 0; i < 36; i++) w[i] = phi_pair(w[i]);
}
__device__ __forceinline__ uint32_t qscale_pair(uint32_t w) {
    const float qs = 0.23570226039551584f * 1.4426950408889634f;
    return pack_bf16(bf_lo(w) * qs, bf_hi(w) * qs);
}
__device__ __forceinline__ void sts32(uint32_t addr, uint32_t v) { asm volatile("st.shared.b32 [%0], %1;" :: "r"(addr), "r"(v) : "memory"); }

__global__ void __launch_bounds__(256, 1)
qkv_kernel(const __grid_constant__ CUtensorMap mapX, const __grid_constant__ CUtensorMap mapWA, const __grid_constant__ CUtensorMap mapWA2,
           const __grid_constant__ CUtensorMap mapWB, const __grid_constant__ CUtensorMap mapWB2) {
    extern __shared__ unsigned char smem_raw[];
    __shared__ __align__(8) uint64_t bars[2 * K1_STAGES];
    __shared__ uint32_t s_nmax[12];
    const uint32_t sbase = (smem_u32(smem_raw) + 1023u) & ~1023u;
    unsigned char* stg = smem_raw + (sbase - smem_u32(smem_raw));
    const uint32_t full0 = smem_u32(bars), empty0 = full0 + 8 * K1_STAGES;
    const int mt = blockIdx.x >> 4, nt = blockIdx.x & 15;
    const int branch = nt >> 3, n0 = (nt & 7) * 216, m0 = mt * 256;
    const int wg = threadIdx.x >> 7;
    const int warp = (threadIdx.x >> 5) & 3, lane = threadIdx.x & 31, g = lane >> 2, t = lane & 3;
    TSTAMP(0, 0);
    const CUtensorMap* w1 = branch ? &mapWB : &mapWA;
    const CUtensorMap* w2 = branch ? &mapWB2 : &mapWA2;
    auto issue = [&](int kt, int part) {
        const int s = kt % K1_STAGES;
        const uint32_t st = sbase + s * K1_STAGE_BYTES, fb = full0 + 8 * s;
        if (part == 0) {
            mbar_expect_tx(fb, K1_STAGE_BYTES);
            tma_2d(st, &mapX, kt * 64, m0, fb);
            tma_2d(st + 32768 + 24576, w2, n0 + 192, kt * 64, fb);
        } else {
            tma_2d(st + 32768, w1, n0, kt * 64, fb);
            tma_2d(st + 32768 + 8192, w1, n0 + 64, kt * 64, fb);
            tma_2d(st + 32768 + 16384, w1, n0 + 128, kt * 64, fb);
        }
    };
    if (threadIdx.x == 0) {
        for (int i = 0; i < K1_STAGES; i++) { mbar_init(full0 + 8 * i, 1); mbar_init(empty0 + 8 * i, 2); }
        asm volatile("fence.mbarrier_init.release.cluster;" ::: "memory");
        issue(0, 0); issue(0, 1);
    }
    if (threadIdx.x >= 64 && threadIdx.x < 76) s_nmax[threadIdx.x - 64] = 0;
    if (blockIdx.x == 0 && threadIdx.x >= 32 && threadIdx.x < 64) g_kvflag[threadIdx.x - 32] = 0;
    __syncthreads();
    if (lane == 0 && threadIdx.x < 128) issue(1 + (threadIdx.x >> 6), (threadIdx.x >> 5) & 1);
    pdl_launch();
    const uint32_t hiA = 64u | 0x40000000u;
    const uint32_t hiB = 64u | 0x40000000u;
    const uint32_t hiB2 = 32u | 0x80000000u;
    float acc0[96], acc1[96], acd0[12], acd1[12];
    #pragma unroll
    for (int i = 0; i < 96; i++) { acc0[i] = 0.f; acc1[i] = 0.f; }
    #pragma unroll
    for (int i = 0; i < 12; i++) { acd0[i] = 0.f; acd1[i] = 0.f; }
    fence_regs(acc0); fence_regs(acc1); fence_regs(acd0); fence_regs(acd1);
    #pragma unroll 1
    for (int kt = 0; kt < 9; kt++) {
        const int s = kt % K1_STAGES;
        mbar_wait_w(full0 + 8 * s, (kt / K1_STAGES) & 1);
        const uint32_t st = sbase + s * K1_STAGE_BYTES;
        const uint32_t a_lo = ((st + wg * 16384) >> 4) | (1u << 16);
        const uint32_t b_lo = ((st + 32768) >> 4) | (512u << 16);
        const uint32_t b2_lo = ((st + 32768 + 24576) >> 4) | (1u << 16);
        WG_FENCE();
        #pragma unroll
        for (int kk = 0; kk < 4; kk++) {
            wgmma_n192_ss(acc0, mkdesc(a_lo + kk * 2, hiA), mkdesc(b_lo + kk * 128, hiB), 1);
            wgmma_n24_ss<0, 1>(acd0, mkdesc(a_lo + kk * 2, hiA), mkdesc(b2_lo + kk * 64, hiB2), 1);
            wgmma_n192_ss(acc1, mkdesc(a_lo + 512 + kk * 2, hiA), mkdesc(b_lo + kk * 128, hiB), 1);
            wgmma_n24_ss<0, 1>(acd1, mkdesc(a_lo + 512 + kk * 2, hiA), mkdesc(b2_lo + kk * 64, hiB2), 1);
        }
        WG_COMMIT();
        WG_WAIT(1);
        if (kt > 0 && kt + 2 < 9) {
            const int sp = (kt - 1) % K1_STAGES;
            if ((threadIdx.x & 127) == 0) mbar_arrive(empty0 + 8 * sp);
            if (threadIdx.x < 32) {
                mbar_wait_w(empty0 + 8 * sp, ((kt - 1) / K1_STAGES) & 1);
                if (lane == 0) { issue(kt + 2, 0); issue(kt + 2, 1); }
            }
            __syncwarp();
        }
    }
    WG_WAIT(0);
    fence_regs(acc0); fence_regs(acc1); fence_regs(acd0); fence_regs(acd1);
    TSTAMP(0, 1);
    __syncthreads();
    {
        const int rgb = wg * 16 + warp * 2;
        const int k0 = branch * 3 + n0 / 576, k1 = branch * 3 + (n0 + 72) / 576, k2 = branch * 3 + (n0 + 144) / 576;
        const int row = threadIdx.x;
        if (k2 == 2) {
            const uint32_t pa = sbase + (row >> 3) * 384 + 256 + (row & 7) * 16 + 4;
            #pragma unroll
            for (int hh = 0; hh < 12; hh++) {
                if ((hh < 4 ? k0 : hh < 8 ? k1 : k2) == 2) {
                    sts32(pa + hh * 12288, 0x00003F80u);
                    asm volatile("st.shared.v2.b32 [%0], {%1, %1};" :: "r"(pa + hh * 12288 + 4), "r"(0u) : "memory");
                }
            }
        }
        auto flush = [&](int grp) {
            fence_async();
            __syncthreads();
            if (lane == 0 && threadIdx.x < 128) {
                const int hh = grp * 4 + (threadIdx.x >> 5), col0 = n0 + hh * 18;
                const int type = col0 / 576, head = (col0 % 576) / 18, kind = branch * 3 + type;
                const bool padded = kind == 1 || kind == 2;
                const size_t hb = padded ? (size_t)(NH + 2 * head) * HEAD_ELEMS + mt * 12288 + (kind - 1) * 6144
                                         : (size_t)(kind * NH + head) * HEAD_ELEMS + mt * 4608;
                asm volatile("cp.async.bulk.global.shared::cta.bulk_group [%0], [%1], %2;" :: "l"(g_T + hb), "r"(sbase + hh * 12288), "r"(padded ? 12288 : 9216) : "memory");
                asm volatile("cp.async.bulk.commit_group;" ::: "memory");
            }
            __syncwarp();
        };
        #pragma unroll
        for (int grp = 0; grp < 3; grp++) {
            uint32_t w[36];
            #pragma unroll
            for (int jj = 0; jj < 9; jj++) {
                const int j = grp * 9 + jj;
                if (j < 24) {
                    w[4 * jj] = pack_bf16(acc0[(4 * j) % 96], acc0[(4 * j + 1) % 96]); w[4 * jj + 1] = pack_bf16(acc0[(4 * j + 2) % 96], acc0[(4 * j + 3) % 96]);
                    w[4 * jj + 2] = pack_bf16(acc1[(4 * j) % 96], acc1[(4 * j + 1) % 96]); w[4 * jj + 3] = pack_bf16(acc1[(4 * j + 2) % 96], acc1[(4 * j + 3) % 96]);
                } else {
                    w[4 * jj] = pack_bf16(acd0[(4 * j) % 12], acd0[(4 * j + 1) % 12]); w[4 * jj + 1] = pack_bf16(acd0[(4 * j + 2) % 12], acd0[(4 * j + 3) % 12]);
                    w[4 * jj + 2] = pack_bf16(acd1[(4 * j) % 12], acd1[(4 * j + 1) % 12]); w[4 * jj + 3] = pack_bf16(acd1[(4 * j + 2) % 12], acd1[(4 * j + 3) % 12]);
                }
            }
            if (grp == 0 ? k0 == 1 : (grp == 2 && k2 == 1 && k1 != 1)) phi36(w);
            const int kg = grp == 0 ? k0 : grp == 1 ? k1 : k2;
            const bool padded = kg == 1 || kg == 2;
            const uint32_t cstride = padded ? 128u : 4096u, smain = padded ? 384u : 128u;
            const uint32_t bmain = sbase + grp * 49152 + rgb * smain + g * 16, btail = sbase + grp * 49152 + 8192 + (rgb * 8 + g) * 4;
            #pragma unroll
            for (int jj = 0; jj < 9; jj++) {
                const int c = 8 * jj + 2 * t, hh = c / 18, d = c - hh * 18;
                const bool tail = !padded && d == 16;
                const uint32_t a = hh * 12288 + (tail ? btail : bmain + (d >> 3) * cstride + (d & 7) * 2);
                const uint32_t s1 = tail ? 32u : smain;
                sts32(a, w[4 * jj]); sts32(a + s1, w[4 * jj + 1]); sts32(a + 8 * s1, w[4 * jj + 2]); sts32(a + 9 * s1, w[4 * jj + 3]);
            }
            flush(grp);
        }
        TSTAMP(0, 3);
        #pragma unroll 1
        for (int grp = 0; grp < 3; grp++) {
            if ((grp == 0 ? k0 : grp == 1 ? k1 : k2) == 4) {
                #pragma unroll 2
                for (int hq = 0; hq < 4; hq++) {
                    const unsigned char* src = stg + (grp * 4 + hq) * 12288;
                    const uint4 v0 = *(const uint4*)(src + row * 16), v1 = *(const uint4*)(src + 4096 + row * 16);
                    const uint32_t w[9] = {v0.x, v0.y, v0.z, v0.w, v1.x, v1.y, v1.z, v1.w, *(const uint32_t*)(src + 8192 + row * 4)};
                    float n2 = 0.f;
                    #pragma unroll
                    for (int i = 0; i < 9; i++) { const float a = bf_lo(w[i]), b = bf_hi(w[i]); n2 = fmaf(a, a, n2); n2 = fmaf(b, b, n2); }
                    uint32_t nb = __float_as_uint(n2);
                    if (!(n2 >= 0.f)) nb = 0x7F800000u;
                    nb = __reduce_max_sync(0xFFFFFFFFu, nb);
                    if (lane == 0) atomicMax(&s_nmax[grp * 4 + hq], nb);
                }
            }
        }
        __syncthreads();
        if (threadIdx.x < 12) {
            const int col0 = n0 + threadIdx.x * 18;
            if (branch == 1 && col0 / 576 == 1) g_kmax[mt][(col0 % 576) / 18] = __uint_as_float(s_nmax[threadIdx.x]);
        }
        if (lane == 0 && threadIdx.x < 128) asm volatile("cp.async.bulk.wait_group.read 0;" ::: "memory");
    }
    TSTAMP(0, 2);
}

__device__ __forceinline__ uint32_t hfma2(uint32_t a, uint32_t b, uint32_t c) { uint32_t r; asm("fma.rn.f16x2 %0, %1, %2, %3;" : "=r"(r) : "r"(a), "r"(b), "r"(c)); return r; }
__device__ __forceinline__ uint32_t and_or(uint32_t a, uint32_t m, uint32_t o) { uint32_t r; asm("lop3.b32 %0, %1, %2, %3, 0xEA;" : "=r"(r) : "r"(a), "r"(m), "r"(o)); return r; }
__device__ __forceinline__ uint32_t poly_ex2_pair(float t0, float t1) {
    const uint32_t u = __byte_perm(__float_as_uint(t0), __float_as_uint(t1), 0x5410);
    const uint32_t m = and_or(u, 0x03FF03FFu, 0x3C003C00u);
    uint32_t y = hfma2(m, 0x2CFE2CFEu, 0xA019A019u);
    y = hfma2(y, m, 0xB82EB82Eu);
    y = hfma2(y, m, 0x3FCF3FCFu);
    const uint32_t w = u + y + 0xC203C204u;
    return and_or(w >> 3, 0x1FFF1FFFu, 0x20002000u);
}

template<int B0, int NB>
__device__ __forceinline__ void softmax_blocks(float (&s)[64], uint32_t (&p)[32]) {
    #pragma unroll
    for (int i = B0 * 4; i < (B0 + NB) * 4; i++) asm volatile("" : "+f"(s[i]) :: "memory");
    #pragma unroll
    for (int b = B0; b < B0 + NB; b++) {
        if ((POLY_BLK >> b) & 1) {
            p[2 * b + 0] = poly_ex2_pair(s[4 * b], s[4 * b + 1]);
            p[2 * b + 1] = poly_ex2_pair(s[4 * b + 2], s[4 * b + 3]);
        } else {
            p[2 * b + 0] = pack_bf16(ex2f(s[4 * b]), ex2f(s[4 * b + 1]));
            p[2 * b + 1] = pack_bf16(ex2f(s[4 * b + 2]), ex2f(s[4 * b + 3]));
        }
    }
}

__device__ __forceinline__ void store_o(int branch, int row0, int h, int t, const float (&o)[12], float r0, float r1) {
    uint32_t* p = (uint32_t*)g_O + ((((branch * 16 + (row0 >> 7)) * 8 + (h >> 2)) * 16 + ((row0 >> 3) & 15)) * 72 + (row0 & 7)) * 4;
    uint32_t* q = p + (h & 3) * 64 + t;
    q[0] = pack_bf16(o[0] * r0, o[1] * r0); q[288] = pack_bf16(o[2] * r1, o[3] * r1);
    q[32] = pack_bf16(o[4] * r0, o[5] * r0); q[288 + 32] = pack_bf16(o[6] * r1, o[7] * r1);
    if (t == 0) { p[256 + (h & 3)] = pack_bf16(o[8] * r0, o[9] * r0); p[288 + 256 + (h & 3)] = pack_bf16(o[10] * r1, o[11] * r1); }
}

__device__ __forceinline__ void load_q(uint32_t (&q)[6], int h, int row0, int t) {
    const char* qb = (const char*)(g_T + (size_t)(3 * NH + h) * HEAD_ELEMS) + (row0 >> 8) * 9216;
    const uint32_t* q0 = (const uint32_t*)(qb + (row0 & 255) * 16) + t;
    q[0] = q0[0]; q[1] = q0[32]; q[2] = q0[1024]; q[3] = q0[1024 + 32];
    const uint32_t* qt = (const uint32_t*)(qb + 8192) + (row0 & 255);
    q[4] = t == 0 ? qt[0] : 0u; q[5] = t == 0 ? qt[8] : 0u;
}

#define K2_SMEM (2 * HEAD_BYTES + 24576 + 1536 + 1024)

__global__ void __launch_bounds__(512, 1)
attn_kernel(const __nv_bfloat16* __restrict__ x, const __nv_bfloat16* __restrict__ gate_w,
            const __nv_bfloat16* __restrict__ woA, const __nv_bfloat16* __restrict__ woB) {
    extern __shared__ unsigned char smem_raw[];
    __shared__ __align__(8) uint64_t bars[16];
    const uint32_t sK = (smem_u32(smem_raw) + 1023u) & ~1023u;
    const uint32_t sV = sK + HEAD_BYTES;
    unsigned char* sgen = smem_raw + (sK - smem_u32(smem_raw));
    TSTAMP(1, 0);
    const uint32_t bar0 = smem_u32(bars);
    const int wg = threadIdx.x >> 7, warp = (threadIdx.x >> 5) & 3, lane = threadIdx.x & 31, g = lane >> 2, t = lane & 3;
    if (threadIdx.x == 0) {
        for (int i = 0; i < 16; i++) mbar_init(bar0 + 8 * i, 1);
        asm volatile("fence.mbarrier_init.release.cluster;" ::: "memory");
    }
    __syncthreads();
    pdl_launch();
    const uint32_t kd0 = (sK >> 4) | (256u << 16);
    const uint32_t kd1 = ((sK + 8192) >> 4);
    const uint32_t khi = 8;
    const uint32_t vd0 = (sV >> 4) | (8u << 16);
    const uint32_t vhi = 256;
    const uint32_t phi8 = 8;

    if (blockIdx.x < 4) {
        const int w16 = blockIdx.x * 4 + wg;
        const int hd0 = w16 < 8 ? w16 : w16 < 12 ? w16 + 8 : w16 + 16, hd1 = w16 < 8 ? w16 + 8 : w16 + 12;
        const int tid = threadIdx.x & 127;
        {
            if (threadIdx.x < 8) asm volatile("cp.async.bulk.prefetch.L2.global [%0], %1;" :: "l"((const char*)((blockIdx.x & 1) ? woB : woA) + ((blockIdx.x >> 1) * 8 + threadIdx.x) * 41472), "r"(41472) : "memory");
            uint32_t gv[9];
            #pragma unroll
            for (int i = 0; i < 9; i++) gv[i] = ((const uint32_t*)gate_w)[lane + 32 * i];
            #pragma unroll 1
            for (int r = blockIdx.x * 512 + (threadIdx.x >> 5) * 8; r < blockIdx.x * 512 + 512; r += 128) {
                uint32_t xv[8][9];
                #pragma unroll
                for (int q = 0; q < 8; q++) {
                    #pragma unroll
                    for (int i = 0; i < 9; i++) xv[q][i] = ((const uint32_t*)(x + (size_t)(r + q) * DM))[lane + 32 * i];
                }
                float sum[8];
                #pragma unroll
                for (int q = 0; q < 8; q++) {
                    sum[q] = 0.f;
                    #pragma unroll
                    for (int i = 0; i < 9; i++) sum[q] += bfr(bf_lo(xv[q][i]) * bf_lo(gv[i])) + bfr(bf_hi(xv[q][i]) * bf_hi(gv[i]));
                }
                #pragma unroll
                for (int o = 16; o > 0; o >>= 1) {
                    #pragma unroll
                    for (int q = 0; q < 8; q++) sum[q] += __shfl_xor_sync(~0u, sum[q], o);
                }
                float z = sum[0];
                #pragma unroll
                for (int q = 1; q < 8; q++) z = lane == q ? sum[q] : z;
                if (lane < 8) g_gate[r + lane] = bfr(1.0f / (1.0f + __expf(-bfr(z))));
            }
        }
        TSTAMP(1, 3);
        pdl_wait();
        TSTAMP(1, 1);
        const uint32_t slot0 = sK + wg * 49152, fb0 = bar0 + wg * 16;
        auto issue = [&](int c) {
            mbar_expect_tx(fb0 + 8 * (c & 1), 24576);
            bulk_g2s(slot0 + (c & 1) * 24576, (const char*)(g_T + (size_t)(NH + 2 * (c < 8 ? hd0 : hd1)) * HEAD_ELEMS) + (size_t)(c & 7) * 24576, 24576, fb0 + 8 * (c & 1));
        };
        if (tid == 0) { issue(0); issue(1); }
        #pragma unroll 1
        for (int hi = 0; hi < 2; hi++) {
            float d1[4][12];
            #pragma unroll
            for (int k = 0; k < 4; k++) {
                #pragma unroll
                for (int i = 0; i < 12; i++) d1[k][i] = 0.f;
                fence_regs(d1[k]);
            }
            #pragma unroll 1
            for (int cc = 0; cc < 8; cc++) {
                const int c = hi * 8 + cc;
                mbar_wait_w(fb0 + 8 * (c & 1), (c >> 1) & 1);
                if (hi == 1) {
                    unsigned char* p = sgen + wg * 49152 + (c & 1) * 24576 + (tid >> 3) * 384 + (tid & 7) * 16;
                    uint4 v0 = *(uint4*)p, v1 = *(uint4*)(p + 128), v2 = *(uint4*)(p + 6144), v3 = *(uint4*)(p + 6144 + 128);
                    uint32_t w0 = *(uint32_t*)(p + 256), w1 = *(uint32_t*)(p + 6144 + 256);
                    v0.x = phi_pair(v0.x); v0.y = phi_pair(v0.y); v0.z = phi_pair(v0.z); v0.w = phi_pair(v0.w);
                    v1.x = phi_pair(v1.x); v1.y = phi_pair(v1.y); v1.z = phi_pair(v1.z); v1.w = phi_pair(v1.w);
                    v2.x = phi_pair(v2.x); v2.y = phi_pair(v2.y); v2.z = phi_pair(v2.z); v2.w = phi_pair(v2.w);
                    v3.x = phi_pair(v3.x); v3.y = phi_pair(v3.y); v3.z = phi_pair(v3.z); v3.w = phi_pair(v3.w);
                    *(uint4*)p = v0; *(uint4*)(p + 128) = v1; *(uint4*)(p + 6144) = v2; *(uint4*)(p + 6144 + 128) = v3;
                    *(uint32_t*)(p + 256) = phi_pair(w0); *(uint32_t*)(p + 6144 + 256) = phi_pair(w1);
                    fence_async();
                    named_bar(1 + wg, 128);
                }
                const uint32_t base = ((slot0 + (c & 1) * 24576) >> 4) | (24u << 16);
                WG_FENCE();
                #pragma unroll
                for (int ks = 0; ks < 16; ks++)
                    wgmma_n24_ss<1, 1>(d1[ks & 3], mkdesc(base + ks * 48, 8u), mkdesc(base + 768 + ks * 48, phi8), 1);
                WG_COMMIT();
                WG_WAIT(0);
                named_bar(1 + wg, 128);
                if (tid == 0 && c + 2 < 16) issue(c + 2);
            }
            #pragma unroll
            for (int k = 0; k < 4; k++) fence_regs(d1[k]);
            #pragma unroll
            for (int i = 0; i < 12; i++) d1[0][i] = (d1[0][i] + d1[1][i]) + (d1[2][i] + d1[3][i]);
            if (warp < 2) {
                const int d = warp * 16 + g;
                uint32_t* kp = (uint32_t*)(g_kv + (hi ? hd1 : hd0) * 768 + (d >> 3) * 192 + (d & 7) * 8 + 2 * t);
                #pragma unroll
                for (int j = 0; j < 3; j++) {
                    kp[32 * j] = d < 18 ? pack_bf16(d1[0][4 * j], d1[0][4 * j + 1]) : 0u;
                    kp[96 + 32 * j] = warp == 0 ? pack_bf16(d1[0][4 * j + 2], d1[0][4 * j + 3]) : 0u;
                }
                __threadfence();
            }
            named_bar(1 + wg, 128);
            if (tid == 0) asm volatile("st.release.gpu.global.b32 [%0], %1;" :: "l"(g_kvflag + (hi ? hd1 : hd0)), "r"(1) : "memory");
        }
        TSTAMP(1, 4);
        TSTAMP(1, 2);
        return;
    }
    const int cta = blockIdx.x - 4;

    const int h = cta >> 2, quarter = cta & 3;
    const uint32_t sPQ = sK + 2 * HEAD_BYTES, sKVt = sPQ + 24576;
    pdl_wait();
    TSTAMP(1, 1);
    auto issue_kv = [&](int c) {
        mbar_expect_tx(bar0 + 8 * c, 16384);
        bulk_g2s(sK + c * 12288, (const char*)(g_T + (size_t)(4 * NH + h) * HEAD_ELEMS) + c * 9216, 8192, bar0 + 8 * c);
        bulk_g2s(sV + c * 12288, (const char*)(g_T + (size_t)(5 * NH + h) * HEAD_ELEMS) + c * 9216, 8192, bar0 + 8 * c);
    };
    int kv_state = 0;
    auto kv_poll = [&](bool block) {
        if (threadIdx.x == 0 && kv_state != 2) {
            while (block && kv_state == 0) asm volatile("ld.acquire.gpu.global.b32 %0, [%1];" : "=r"(kv_state) : "l"(g_kvflag + h) : "memory");
            if (kv_state == 1) {
                asm volatile("fence.proxy.async.global;" ::: "memory");
                mbar_expect_tx(bar0 + 72, 1536);
                bulk_g2s(sKVt, g_kv + h * 768, 1536, bar0 + 72);
                kv_state = 2;
            } else {
                asm volatile("ld.acquire.gpu.global.b32 %0, [%1];" : "=r"(kv_state) : "l"(g_kvflag + h) : "memory");
            }
        }
    };
    float km2 = 0.f;
    #pragma unroll
    for (int i = 0; i < 8; i++) km2 = fmaxf(km2, g_kmax[i][h]);
    int s_fast_tmp = 0;
    uint32_t zr = 0u;
    asm volatile("" : "+r"(zr));
    uint32_t qf[2][6];
    #pragma unroll
    for (int pass = 0; pass < 2; pass++) {
        const int row0 = quarter * 512 + (wg * 2 + pass) * 64 + warp * 16 + g;
        load_q(qf[pass], h, row0, t);
    }
    uint32_t ktl[4], vtl[4];
    #pragma unroll
    for (int i = 0; i < 4; i++) {
        const int key = threadIdx.x + i * 512;
        ktl[i] = *(const uint32_t*)((const char*)(g_T + (size_t)(4 * NH + h) * HEAD_ELEMS) + (key >> 8) * 9216 + 8192 + (key & 255) * 4);
        vtl[i] = *(const uint32_t*)((const char*)(g_T + (size_t)(5 * NH + h) * HEAD_ELEMS) + (key >> 8) * 9216 + 8192 + (key & 255) * 4);
    }
    if (threadIdx.x == 0) issue_kv(0);
    if (threadIdx.x == 128) issue_kv(1);
    __syncwarp();
    #pragma unroll
    for (int i = 0; i < 6; i++) { qf[0][i] = qscale_pair(qf[0][i]); qf[1][i] = qscale_pair(qf[1][i]); }
    float mrow[2][2];
    bool ok = true;
    #pragma unroll
    for (int pass = 0; pass < 2; pass++) {
        auto sq = [](uint32_t v) { float a = bf_lo(v), b = bf_hi(v); return a * a + b * b; };
        float n0 = sq(qf[pass][0]) + sq(qf[pass][2]) + sq(qf[pass][4]);
        float n1 = sq(qf[pass][1]) + sq(qf[pass][3]) + sq(qf[pass][5]);
        n0 += __shfl_xor_sync(~0u, n0, 1); n0 += __shfl_xor_sync(~0u, n0, 2);
        n1 += __shfl_xor_sync(~0u, n1, 1); n1 += __shfl_xor_sync(~0u, n1, 2);
        mrow[pass][0] = sqrtf(n0 * km2) * 1.01f + 0.01f;
        mrow[pass][1] = sqrtf(n1 * km2) * 1.01f + 0.01f;
        ok = ok && (mrow[pass][0] <= 31.0f) && (mrow[pass][1] <= 31.0f);
    }
    #pragma unroll
    for (int i = 0; i < 4; i++) {
        const int key = threadIdx.x + i * 512;
        const uint32_t a = (key >> 8) * 12288 + 8192 + (key & 255) * 16;
        const uint32_t pmagic = ((POLY_BLK >> ((key & 127) >> 3)) & 1) ? 0x46013F80u : 0x3F803F80u;
        asm volatile("st.shared.v4.b32 [%0], {%1, %2, %3, %3};" :: "r"(sK + a), "r"(ktl[i]), "r"(pmagic), "r"(0u) : "memory");
        asm volatile("st.shared.v4.b32 [%0], {%1, %2, %3, %3};" :: "r"(sV + a), "r"(vtl[i]), "r"(0x00003F80u), "r"(0u) : "memory");
    }
    fence_async();
    __syncthreads();
    bool fast;
    asm volatile("{\n.reg .pred p, q;\nsetp.ne.b32 p, %1, 0;\nbar.red.and.pred q, %2, 128, p;\nselp.b32 %0, 1, 0, q;\n}\n"
                 : "=r"(*(int*)&s_fast_tmp) : "r"((int)ok), "r"(1 + wg) : "memory");
    fast = __all_sync(0xFFFFFFFFu, s_fast_tmp != 0);
    TSTAMP(1, 3);

    #pragma unroll 1
    for (int pass = 0; pass < 2; pass++) {
        const int row0 = quarter * 512 + (wg * 2 + pass) * 64 + warp * 16 + g;
        uint32_t qa[6];
        #pragma unroll
        for (int i = 0; i < 6; i++) qa[i] = pass ? qf[1][i] : qf[0][i];
        float o[12];
        #pragma unroll
        for (int i = 0; i < 12; i++) o[i] = 0.f;
        fence_regs(o);
        float s[64]; uint32_t p[32];
        #pragma unroll
        for (int i = 0; i < 64; i++) s[i] = 0.f;
        fence_regs(s);
        if (fast) {
            if (t == 1) { qa[4] = pack_bf16(-(pass ? mrow[1][0] : mrow[0][0]), 1.0f); qa[5] = pack_bf16(-(pass ? mrow[1][1] : mrow[0][1]), 1.0f); }
            #pragma unroll 1
            for (int j = 0; j < 16; j++) {
                if (pass == 0 && (j & 1) == 0) {
                    const int cn = (j >> 1) + 2;
                    if ((threadIdx.x & 127) == 0 && (cn & 3) == wg) {
                        if (cn < 8) issue_kv(cn);
                        else if (cn == 8) {
                            mbar_expect_tx(bar0 + 64, 16384);
                            bulk_g2s(sPQ, (const char*)(g_T + (size_t)h * HEAD_ELEMS) + quarter * 18432, 8192, bar0 + 64);
                            bulk_g2s(sPQ + 12288, (const char*)(g_T + (size_t)h * HEAD_ELEMS) + quarter * 18432 + 9216, 8192, bar0 + 64);
                        }
                    }
                    mbar_wait_w(bar0 + 8 * (j >> 1), 0);
                }
                const uint32_t ko = (j >> 1) * 768 + (j & 1) * 128;
                WG_FENCE();
                wgmma_n128_rs<0>(s, qa[0], qa[1], qa[2], qa[3], mkdesc(kd0 + ko, khi));
                wgmma_n128_rs<1>(s, qa[4], qa[5], zr, zr, mkdesc(kd1 + ko, khi));
                WG_COMMIT();
                if (pass == 1 && (j & 3) == 3) { kv_poll(false); __syncwarp(); }
                WG_WAIT(0);
                #pragma unroll
                for (int qd = 0; qd < 4; qd++) {
                    if (qd == 0) softmax_blocks<0, 4>(s, p);
                    if (qd == 1) softmax_blocks<4, 4>(s, p);
                    if (qd == 2) softmax_blocks<8, 4>(s, p);
                    if (qd == 3) softmax_blocks<12, 4>(s, p);
                    WG_FENCE();
                    wgmma_n24_rs(o, p[qd * 8 + 0], p[qd * 8 + 1], p[qd * 8 + 2], p[qd * 8 + 3], mkdesc(vd0 + ko + qd * 32, vhi));
                    wgmma_n24_rs(o, p[qd * 8 + 4], p[qd * 8 + 5], p[qd * 8 + 6], p[qd * 8 + 7], mkdesc(vd0 + ko + qd * 32 + 16, vhi));
                    WG_COMMIT();
                }
                WG_WAIT(0);
            }
        } else {
            {
                load_q(qa, h, row0, t);
            }
            const float qs = 0.23570226039551584f * 1.4426950408889634f;
            float mr0 = -INFINITY, mr1 = -INFINITY;
            #pragma unroll 1
            for (int j = 0; j < 16; j++) {
                if (pass == 0 && (j & 1) == 0) {
                    const int cn = (j >> 1) + 2;
                    if ((threadIdx.x & 127) == 0 && (cn & 3) == wg) {
                        if (cn < 8) issue_kv(cn);
                        else if (cn == 8) {
                            mbar_expect_tx(bar0 + 64, 16384);
                            bulk_g2s(sPQ, (const char*)(g_T + (size_t)h * HEAD_ELEMS) + quarter * 18432, 8192, bar0 + 64);
                            bulk_g2s(sPQ + 12288, (const char*)(g_T + (size_t)h * HEAD_ELEMS) + quarter * 18432 + 9216, 8192, bar0 + 64);
                        }
                    }
                    mbar_wait_w(bar0 + 8 * (j >> 1), 0);
                }
                const uint32_t ko = (j >> 1) * 768 + (j & 1) * 128;
                WG_FENCE();
                wgmma_n128_rs<0>(s, qa[0], qa[1], qa[2], qa[3], mkdesc(kd0 + ko, khi));
                wgmma_n128_rs<1>(s, qa[4], qa[5], zr, zr, mkdesc(kd1 + ko, khi));
                WG_COMMIT();
                WG_WAIT(0);
                fence_regs(s); fence_regs(o);
                float x0 = mr0, x1 = mr1;
                #pragma unroll
                for (int b = 0; b < 16; b++) {
                    x0 = fmaxf(x0, fmaxf(s[4 * b], s[4 * b + 1]));
                    x1 = fmaxf(x1, fmaxf(s[4 * b + 2], s[4 * b + 3]));
                }
                x0 = fmaxf(x0, __shfl_xor_sync(~0u, x0, 1)); x0 = fmaxf(x0, __shfl_xor_sync(~0u, x0, 2));
                x1 = fmaxf(x1, __shfl_xor_sync(~0u, x1, 1)); x1 = fmaxf(x1, __shfl_xor_sync(~0u, x1, 2));
                const float c0 = exp2f((mr0 - x0) * qs), c1 = exp2f((mr1 - x1) * qs);
                mr0 = x0; mr1 = x1;
                #pragma unroll
                for (int i = 0; i < 12; i++) o[i] *= (i & 2) ? c1 : c0;
                #pragma unroll
                for (int b = 0; b < 16; b++) {
                    p[2 * b] = pack_bf16(exp2f((s[4 * b] - x0) * qs), exp2f((s[4 * b + 1] - x0) * qs));
                    p[2 * b + 1] = pack_bf16(exp2f((s[4 * b + 2] - x1) * qs), exp2f((s[4 * b + 3] - x1) * qs));
                }
                fence_regs(o);
                WG_FENCE();
                #pragma unroll
                for (int kk = 0; kk < 8; kk++)
                    wgmma_n24_rs(o, p[kk * 4 + 0], p[kk * 4 + 1], p[kk * 4 + 2], p[kk * 4 + 3], mkdesc(vd0 + ko + kk * 16, vhi));
                WG_COMMIT();
                WG_WAIT(0);
            }
        }
        fence_regs(o);
        const float l0 = __shfl_sync(~0u, o[8], (lane & ~3) | 1);
        const float l1 = __shfl_sync(~0u, o[10], (lane & ~3) | 1);
        store_o(1, row0, h, t, o, 1.0f / l0, 1.0f / l1);
        if (pass == 0) {
            constexpr int PER = 82944 / 128, NQ = (PER + 511) / 512;
            uint4 wv[NQ];
            #pragma unroll
            for (int q = 0; q < NQ; q++) {
                const int id = cta * PER + threadIdx.x + q * 512;
                if (threadIdx.x + q * 512 < PER) wv[q] = *(const uint4*)((id >= 41472 ? woB - 41472 * 8 : woA) + (size_t)id * 8);
            }
            #pragma unroll
            for (int q = 0; q < NQ; q++) {
                const int id = cta * PER + threadIdx.x + q * 512;
                const int b = id >= 41472, r2 = id - b * 41472, k = r2 / 72, c = r2 % 72;
                const int hh = k / 18, d = k % 18;
                const int kp = (hh >> 2) * 72 + (d < 16 ? (hh & 3) * 16 + d : 64 + (hh & 3) * 2 + (d - 16));
                if (threadIdx.x + q * 512 < PER) *(uint4*)(g_Wt + ((((c / 24) * 2 + b) * 8 + kp / 72) * 24 + (c % 24)) * 576 + (kp % 72) * 8) = wv[q];
            }
        }
    }
    TSTAMP(1, 4);
    {
        const uint32_t qtl = *(const uint32_t*)((const char*)(g_T + (size_t)h * HEAD_ELEMS) + (quarter * 2 + (wg >> 1)) * 9216 + 8192 + ((wg & 1) * 128 + (threadIdx.x & 127)) * 4);
        kv_poll(true); kv_poll(true);
        mbar_wait_w(bar0 + 64, 0);
        {
            const int tid = threadIdx.x & 127, r = (wg & 1) * 128 + tid;
            unsigned char* pq = sgen + 2 * HEAD_BYTES + (wg >> 1) * 12288 + r * 16;
            uint4 v0 = *(uint4*)pq, v1 = *(uint4*)(pq + 4096);
            v0.x = phi_pair(v0.x); v0.y = phi_pair(v0.y); v0.z = phi_pair(v0.z); v0.w = phi_pair(v0.w);
            v1.x = phi_pair(v1.x); v1.y = phi_pair(v1.y); v1.z = phi_pair(v1.z); v1.w = phi_pair(v1.w);
            *(uint4*)pq = v0; *(uint4*)(pq + 4096) = v1;
            *(uint4*)(pq + 8192) = make_uint4(phi_pair(qtl), 0u, 0u, 0u);
            fence_async();
        }
        named_bar(1 + wg, 128);
        mbar_wait_w(bar0 + 72, 0);
        float e[4][12];
        #pragma unroll
        for (int k = 0; k < 4; k++) {
            #pragma unroll
            for (int i = 0; i < 12; i++) e[k][i] = 0.f;
            fence_regs(e[k]);
        }
        const uint32_t ab = (sPQ + (wg >> 1) * 12288 + (wg & 1) * 2048) >> 4, bb = (sKVt >> 4) | (24u << 16);
        WG_FENCE();
        wgmma_n24_ss<0, 1>(e[0], mkdesc(ab | (256u << 16), khi), mkdesc(bb, phi8), 0);
        wgmma_n24_ss<0, 1>(e[1], mkdesc((ab + 64) | (256u << 16), khi), mkdesc(bb, phi8), 0);
        wgmma_n24_ss<0, 1>(e[2], mkdesc(ab + 512, khi), mkdesc(bb + 48, phi8), 0);
        wgmma_n24_ss<0, 1>(e[3], mkdesc(ab + 64 + 512, khi), mkdesc(bb + 48, phi8), 0);
        WG_COMMIT();
        WG_WAIT(0);
        #pragma unroll
        for (int k = 0; k < 4; k++) fence_regs(e[k]);
        #pragma unroll
        for (int m = 0; m < 2; m++) {
            #pragma unroll
            for (int i = 0; i < 12; i++) e[m][i] = bfr(e[m][i] + e[m + 2][i]);
            const float l0 = __shfl_sync(~0u, e[m][8], (lane & ~3) | 1), l1 = __shfl_sync(~0u, e[m][10], (lane & ~3) | 1);
            store_o(0, quarter * 512 + (wg * 2 + m) * 64 + warp * 16 + g, h, t, e[m], 1.0f / bfr(l0 + 1e-6f), 1.0f / bfr(l1 + 1e-6f));
        }
    }
    TSTAMP(1, 2);
}

#define K3_UNITS 4
#define K3_UNIT_BYTES 46080
#define K3_SMEM (K3_UNITS * K3_UNIT_BYTES + 26624 + 1024)

__global__ void __cluster_dims__(2, 1, 1) __launch_bounds__(288, 1)
out_kernel(__nv_bfloat16* __restrict__ out) {
    extern __shared__ unsigned char smem_raw[];
    __shared__ __align__(8) uint64_t bars[2 * K3_UNITS + 8];
    const uint32_t sA = (smem_u32(smem_raw) + 1023u) & ~1023u;
    const uint32_t sX = sA + K3_UNITS * K3_UNIT_BYTES;
    const uint32_t full0 = smem_u32(bars), empty0 = full0 + 8 * K3_UNITS;
    const int br = blockIdx.x & 1, tile = blockIdx.x >> 1, mt = tile / 3, nt = tile % 3;
    const int m0 = mt * 128, n0 = nt * 192;
    TSTAMP(2, 0);
    if (threadIdx.x == 0) {
        for (int i = 0; i < K3_UNITS; i++) { mbar_init(full0 + 8 * i, 1); mbar_init(empty0 + 8 * i, 2); }
        for (int i = 0; i < 8; i++) mbar_init(full0 + 16 * K3_UNITS + 8 * i, 1);
        asm volatile("fence.mbarrier_init.release.cluster;" ::: "memory");
    }
    __syncthreads();
    cluster_arrive();
    TSTAMP(2, 3);
    pdl_wait();
    TSTAMP(2, 1);
    const int wg = threadIdx.x >> 7;
    if (wg == 2) {
        if (threadIdx.x == 256) {
            for (int c = 0; c < 8; c++) {
                const int s = c % K3_UNITS;
                if (c >= K3_UNITS) mbar_wait(empty0 + 8 * s, 0);
                const uint32_t st = sA + s * K3_UNIT_BYTES;
                mbar_expect_tx(full0 + 8 * s, K3_UNIT_BYTES);
                bulk_g2s(st, g_O + (size_t)((br * 16 + mt) * 8 + c) * 9216, 18432, full0 + 8 * s);
                bulk_g2s(st + 18432, g_Wt + (size_t)((nt * 2 + br) * 8 + c) * 13824, 27648, full0 + 8 * s);
            }
        }
        __syncwarp();
        cluster_wait();
        cluster_arrive();
    } else {
        const int warp = (threadIdx.x >> 5) & 3, lane = threadIdx.x & 31, g = lane >> 2, t = lane & 3;
        float acc[96];
        #pragma unroll
        for (int i = 0; i < 96; i++) acc[i] = 0.f;
        fence_regs(acc);
        const uint32_t hiA = 72u;
        const uint32_t hiB = 72u;
        const int r0 = m0 + wg * 64 + warp * 16 + g;
        float g0 = g_gate[r0], g1 = g_gate[r0 + 8];
        if (br) { g0 = bfr(1.0f - g0); g1 = bfr(1.0f - g1); }
        #pragma unroll 1
        for (int pr = 0; pr < 4; pr++) {
            const int s = (pr & 1) * 2;
            const uint32_t a_lo = ((sA + s * K3_UNIT_BYTES + wg * 9216) & 0x3FFFF) >> 4;
            const uint32_t b_lo = ((sA + s * K3_UNIT_BYTES + 18432) & 0x3FFFF) >> 4;
            mbar_wait_w(full0 + 8 * s, pr >> 1);
            if (pr == 0) TSTAMP(2, 4);
            WG_FENCE();
            #pragma unroll
            for (int i = 0; i < 4; i++) wgmma_n192_ss(acc, mkdesc((a_lo + i * 16) | (8u << 16), hiA), mkdesc((b_lo + i * 16) | (8u << 16), hiB), 1);
            WG_COMMIT();
            mbar_wait_w(full0 + 8 * s + 8, pr >> 1);
            WG_FENCE();
            wgmma_n192_ss(acc, mkdesc((a_lo + 64) | ((K3_UNIT_BYTES / 16 - 64) << 16), hiA), mkdesc((b_lo + 64) | ((K3_UNIT_BYTES / 16 - 64) << 16), hiB), 1);
            #pragma unroll
            for (int i = 0; i < 4; i++)
                wgmma_n192_ss(acc, mkdesc((a_lo + K3_UNIT_BYTES / 16 + 8 + i * 16) | (8u << 16), hiA), mkdesc((b_lo + K3_UNIT_BYTES / 16 + 8 + i * 16) | (8u << 16), hiB), 1);
            WG_COMMIT();
            if (pr < 2) {
                WG_WAIT(0);
                if ((threadIdx.x & 127) < 2) mbar_arrive(empty0 + 8 * (s + (threadIdx.x & 1)));
            }
        }
        WG_WAIT(0);
        fence_regs(acc);
        TSTAMP(2, 5);
        uint32_t keep[24];
        named_bar(1, 256);
        const uint32_t snd = sA + (wg * 4 + warp) * 3328;
        #pragma unroll
        for (int j = 0; j < 24; j++) {
            const uint32_t v0 = pack_bf16(g0 * bfr(acc[4 * j]), g0 * bfr(acc[4 * j + 1]));
            const uint32_t v1 = pack_bf16(g1 * bfr(acc[4 * j + 2]), g1 * bfr(acc[4 * j + 3]));
            const int jj = j % 12;
            if ((j < 12) == (br == 0)) { keep[2 * jj] = v0; keep[2 * jj + 1] = v1; }
            else { sts32(snd + g * 208 + jj * 16 + t * 4, v0); sts32(snd + (g + 8) * 208 + jj * 16 + t * 4, v1); }
        }
        fence_async();
        __syncwarp();
        cluster_wait();
        const uint32_t xbar = full0 + 16 * K3_UNITS + 8 * (wg * 4 + warp);
        if (lane == 0) {
            uint32_t rdst, rbar;
            asm volatile("mapa.shared::cluster.u32 %0, %1, %2;" : "=r"(rdst) : "r"(sX + (wg * 4 + warp) * 3328), "r"(br ^ 1));
            asm volatile("mapa.shared::cluster.u32 %0, %1, %2;" : "=r"(rbar) : "r"(xbar), "r"(br ^ 1));
            mbar_expect_tx(xbar, 3328);
            asm volatile("cp.async.bulk.shared::cluster.shared::cta.mbarrier::complete_tx::bytes [%0], [%1], %2, [%3];"
                         :: "r"(rdst), "r"(snd), "r"(3328), "r"(rbar) : "memory");
        }
        mbar_wait_w(xbar, 0);
        cluster_arrive();
        const uint32_t sx = sX + (wg * 64 + warp * 16) * 208;
        #pragma unroll
        for (int jj = 0; jj < 12; jj++) {
            uint32_t p0, p1;
            asm volatile("ld.shared.b32 %0, [%1];" : "=r"(p0) : "r"(sx + g * 208 + jj * 16 + t * 4));
            asm volatile("ld.shared.b32 %0, [%1];" : "=r"(p1) : "r"(sx + (g + 8) * 208 + jj * 16 + t * 4));
            sts32(sx + g * 208 + jj * 16 + t * 4, hadd2_bf16(keep[2 * jj], p0));
            sts32(sx + (g + 8) * 208 + jj * 16 + t * 4, hadd2_bf16(keep[2 * jj + 1], p1));
        }
        __syncwarp();
        #pragma unroll
        for (int i = 0; i < 6; i++) {
            const int id = i * 32 + lane, r = id / 12, c = id % 12;
            uint4 v;
            asm volatile("ld.shared.v4.b32 {%0,%1,%2,%3}, [%4];" : "=r"(v.x), "=r"(v.y), "=r"(v.z), "=r"(v.w) : "r"(sx + r * 208 + c * 16));
            *(uint4*)(out + (size_t)(m0 + wg * 64 + warp * 16 + r) * DM + n0 + br * 96 + c * 8) = v;
        }
        TSTAMP(2, 2);
    }
    cluster_wait();
}

typedef CUresult (*EncodeFn)(CUtensorMap*, CUtensorMapDataType, cuuint32_t, void*, const cuuint64_t*, const cuuint64_t*,
                             const cuuint32_t*, const cuuint32_t*, CUtensorMapInterleave, CUtensorMapSwizzle,
                             CUtensorMapL2promotion, CUtensorMapFloatOOBfill);

static void make_map(EncodeFn enc, CUtensorMap* m, const void* base, uint64_t inner, uint64_t outer, uint32_t box_in, uint32_t box_out, CUtensorMapSwizzle sw) {
    cuuint64_t dims[2] = {inner, outer};
    cuuint64_t strides[1] = {inner * 2};
    cuuint32_t box[2] = {box_in, box_out};
    cuuint32_t es[2] = {1, 1};
    enc(m, CU_TENSOR_MAP_DATA_TYPE_BFLOAT16, 2, (void*)base, dims, strides, box, es, CU_TENSOR_MAP_INTERLEAVE_NONE, sw,
        CU_TENSOR_MAP_L2_PROMOTION_L2_256B, CU_TENSOR_MAP_FLOAT_OOB_FILL_NONE);
}

extern "C" void kernel_launch(void* const* d_in, const int* in_sizes, int n_in, void* d_out, int out_size) {
    const __nv_bfloat16* x = (const __nv_bfloat16*)d_in[0];
    const __nv_bfloat16* wA = (const __nv_bfloat16*)d_in[1];
    const __nv_bfloat16* woA = (const __nv_bfloat16*)d_in[2];
    const __nv_bfloat16* wB = (const __nv_bfloat16*)d_in[4];
    const __nv_bfloat16* woB = (const __nv_bfloat16*)d_in[5];
    const __nv_bfloat16* gw = (const __nv_bfloat16*)d_in[6];
    __nv_bfloat16* out = (__nv_bfloat16*)d_out;

    static EncodeFn enc = nullptr;
    if (!enc) {
        void* fn = nullptr; cudaDriverEntryPointQueryResult st;
        cudaGetDriverEntryPoint("cuTensorMapEncodeTiled", &fn, cudaEnableDefault, &st);
        enc = (EncodeFn)fn;
        cudaFuncSetAttribute(qkv_kernel, cudaFuncAttributeMaxDynamicSharedMemorySize, K1_SMEM);
        cudaFuncSetAttribute(attn_kernel, cudaFuncAttributeMaxDynamicSharedMemorySize, K2_SMEM);
        cudaFuncSetAttribute(out_kernel, cudaFuncAttributeMaxDynamicSharedMemorySize, K3_SMEM);
    }
    CUtensorMap mX, mWA, mWA2, mWB, mWB2;
    make_map(enc, &mX, x, DM, S_LEN, 64, 256, CU_TENSOR_MAP_SWIZZLE_128B);
    make_map(enc, &mWA, wA, 3 * DM, DM, 64, 64, CU_TENSOR_MAP_SWIZZLE_128B);
    make_map(enc, &mWA2, wA, 3 * DM, DM, 32, 64, CU_TENSOR_MAP_SWIZZLE_64B);
    make_map(enc, &mWB, wB, 3 * DM, DM, 64, 64, CU_TENSOR_MAP_SWIZZLE_128B);
    make_map(enc, &mWB2, wB, 3 * DM, DM, 32, 64, CU_TENSOR_MAP_SWIZZLE_64B);

    cudaStream_t stream = cudaStreamPerThread;
    cudaLaunchAttribute at[1];
    at[0].id = cudaLaunchAttributeProgrammaticStreamSerialization;
    at[0].val.programmaticStreamSerializationAllowed = 1;

    qkv_kernel<<<128, 256, K1_SMEM, stream>>>(mX, mWA, mWA2, mWB, mWB2);

    cudaLaunchConfig_t c2 = {};
    c2.gridDim = dim3(132); c2.blockDim = dim3(512); c2.dynamicSmemBytes = K2_SMEM; c2.stream = stream; c2.attrs = at; c2.numAttrs = 1;
    cudaLaunchKernelEx(&c2, attn_kernel, x, gw, woA, woB);

    cudaLaunchConfig_t c3 = {};
    c3.gridDim = dim3(96); c3.blockDim = dim3(288); c3.dynamicSmemBytes = K3_SMEM; c3.stream = stream; c3.attrs = at; c3.numAttrs = 1;
    cudaLaunchKernelEx(&c3, out_kernel, out);
}
```
